```python
import torch

def _softmax(x, axis=-1):
    return torch.softmax(x, dim=axis)
def _gelu(x):
    return torch.nn.functional.gelu(x, approximate="tanh")
def _silu(x):
    return torch.nn.functional.silu(x)
def _sigmoid(x):
    return torch.sigmoid(x)
def _layernorm(x, axis=-1, eps=1e-5):
    m = x.mean(dim=axis, keepdim=True)
    v = x.var(dim=axis, keepdim=True, unbiased=False)
    return (x - m) / torch.sqrt(v + eps)
def _scatter_add(tgt, idx, src, axis=0):
    return tgt.clone().index_add_(axis, idx, src)
def _segment_sum(src, seg, n):
    out = torch.zeros((n,) + src.shape[1:], dtype=src.dtype)
    return out.index_add_(0, seg, src)
def _pad(x, pw):
    flat = tuple(v for pair in reversed(pw) for v in pair)
    return torch.nn.functional.pad(x, flat)

kernel_name = 'sequential_preLN__ssm_conv_h3__glu_gated_geglu__prompt'

def setup_inputs():

    _w = (lambda a: (lambda t: t.to(torch.bfloat16) if t.is_floating_point() else t)(torch.as_tensor(a)))
    def _A_setup():
        B, S, D = 1, 2048, 512
        ks = 4
        return {
            "q": _w((lambda *s: torch.randn(*s, dtype=torch.bfloat16) * 0.05)(B, S, D)),
            "k": _w((lambda *s: torch.randn(*s, dtype=torch.bfloat16) * 0.2)(B, S, D)),
            "v": _w((lambda *s: torch.randn(*s, dtype=torch.bfloat16) * 0.2)(B, S, D)),
            "shift_k": _w((lambda *s: torch.randn(*s, dtype=torch.bfloat16) * 0.2)(D, ks) * 0.5),
            "ssm_k": _w((lambda *s: torch.randn(*s, dtype=torch.bfloat16) * 0.4)(D, S) * (1.0 / S ** 0.5)),
            "ssm_D": _w((lambda *s: torch.randn(*s, dtype=torch.bfloat16) * 0.2)(D)),
        }
    _A_in = _A_setup()

    def _B_setup():
        B, S, Dm, Df = 1, 2048, 512, 1376
        return {
            "x": _w((lambda *s: torch.randn(*s, dtype=torch.bfloat16) * 0.05)(B, S, Dm)),
            "w_gate": _w((lambda *s: torch.randn(*s, dtype=torch.bfloat16) * 0.4)(Dm, Df) * (Dm ** -0.5)),
            "w_up": _w((lambda *s: torch.randn(*s, dtype=torch.bfloat16) * 0.4)(Dm, Df) * (Dm ** -0.5)),
            "w_down": _w((lambda *s: torch.randn(*s, dtype=torch.bfloat16) * 0.4)(Df, Dm) * (Df ** -0.5)),
        }
    _B_in = _B_setup()

    return {
        "A_q": _A_in["q"],
        "A_k": _A_in["k"],
        "A_v": _A_in["v"],
        "A_shift_k": _A_in["shift_k"],
        "A_ssm_k": _A_in["ssm_k"],
        "A_ssm_D": _A_in["ssm_D"],
        "B_x": _B_in["x"],
        "B_w_gate": _B_in["w_gate"],
        "B_w_up": _B_in["w_up"],
        "B_w_down": _B_in["w_down"],
    }

def reference(A_q, A_k, A_v, A_shift_k, A_ssm_k, A_ssm_D, B_x, B_w_gate, B_w_up, B_w_down):
    def _A_ref(q, k, v, shift_k, ssm_k, ssm_D):
        B, S, D = q.shape
        ks = shift_k.shape[-1]
        k_pad = _pad(k, ((0, 0), (ks - 1, 0), (0, 0)))
        k_shift = torch.zeros_like(k)
        for t in range(ks):
            k_shift = k_shift + k_pad[:, t:t + S, :] * shift_k[:, ks - 1 - t][None, None, :]
        kv = k_shift * v
        L = 2 * S
        kv_pad = _pad(kv, ((0, 0), (0, S), (0, 0)))
        kf_pad = _pad(ssm_k, ((0, 0), (0, S)))
        kv_f = (lambda x, axes=(-2,-1): torch.fft.rfft2(x.float(), dim=axes))(kv_pad[:, None, :, :], axes=(1, 2))
        kf_f = (lambda x, axes=(-2,-1): torch.fft.rfft2(x.float(), dim=axes))(kf_pad[:, None, :], axes=(1, 2))
        kf_f = (lambda x, *d: x.permute(*d))(kf_f, 1, 2, 0)
        y_f = kv_f * kf_f[None, :, :, :]
        y = (lambda x, s, axes=(-2,-1): torch.fft.irfft2(x, s=s, dim=axes).to(torch.bfloat16))(y_f, (1, L), axes=(1, 2))[:, 0, :S, :]
        y = y + kv * ssm_D[None, None, :]
        return q * y

    def _B_ref(x, w_gate, w_up, w_down):
        g = torch.einsum("bsd,df->bsf", x, w_gate)
        u = torch.einsum("bsd,df->bsf", x, w_up)
        h = _gelu(g) * u
        return torch.einsum("bsf,fd->bsd", h, w_down)

    x = A_q
    h = x + _A_ref(_layernorm(x, axis=-1), A_k, A_v, A_shift_k, A_ssm_k, A_ssm_D)
    h2 = h + _B_ref(_layernorm(h, axis=-1), B_w_gate, B_w_up, B_w_down)
    return h2
```

```cpp
#include <cuda_runtime.h>
#include <cuda_bf16.h>
#include <cuda.h>
#include <stdint.h>

namespace {

constexpr int S_ = 2048, D_ = 512, F_ = 1376;
constexpr int NCTA = 128, NTHR = 512;
#define FFN_MAP 0
#define STAT_SHIFT 0
#define EPI1_FAST 1
#define R2_DEPTH 2
#define H3_DEPTH 6
#define GPC_MAP 1
#define KV_HOLD 3
#define A_AFTER_GO 1
#define A_DEPTH 4
#define H_DEPTH 2
#define R_DEPTH 2

struct __align__(1024) Scratch {
  uint16_t xT[D_ * S_];
  uint16_t hT[32 * D_ * 64];
  uint16_t H[32 * 86 * 1024];
  uint16_t wX[6 * D_ * 32];
  uint32_t st1[S_];
  float    cs[F_ * 2];
  unsigned cnt[(2 + 16 + 48) * 32];
  unsigned epoch[NCTA];
};
__device__ Scratch g_scr;
#define STAMP(id)
#define STAMP_IF(c, id)
#define TW(acc, stmt) stmt
#define TWOUT(c, id, acc)
#define SSTAMP(c, id)
#define STAMP_NS(c, id)
constexpr int CNT_X = 0, CNT_C = 1, CNT_E = 2, CNT_H = 18;
__host__ __device__ constexpr int tok(int b, int tau) { return 128 * (b >> 1) + 16 * (tau & 7) + 8 * (b & 1) + ((tau >> 3) ^ 1); }

constexpr uint32_t OFF_A    = 0;
constexpr uint32_t OFF_RING = 131072;
constexpr uint32_t OFF_CS   = 229376;
constexpr uint32_t OFF_BAR  = OFF_CS + 1408;
constexpr uint32_t OFF_STX  = OFF_BAR + 640;
constexpr uint32_t SMEM_BYTES = 232448;
constexpr uint32_t KV_PIECE = 8448;
constexpr uint32_t OFF_KV   = 0;
constexpr uint32_t OFF_XR   = 4 * KV_PIECE;
constexpr uint32_t OFF_XTE  = OFF_XR;
constexpr uint32_t OFF_STE  = OFF_XR + 8192;
constexpr uint32_t U_PITCH  = 8352, U_ODD = 4160;
constexpr uint32_t T_PITCH  = 4352;
constexpr uint32_t OFF_TAP  = 65536;
constexpr uint32_t OFF_U    = OFF_TAP + 4 * T_PITCH;
constexpr uint32_t OFF_XTL  = OFF_U + 4 * U_PITCH;
constexpr uint32_t OFF_STL  = OFF_XTL + 8192;
constexpr uint32_t OFF_XST  = OFF_RING + 2 * 16384;
constexpr uint32_t OFF_XCH  = OFF_RING + 3 * 16384;
static_assert(OFF_XR + 8 * 2064 <= 65536, "");
static_assert(OFF_STL + 4096 <= 131072, "");
static_assert(OFF_STX + 1024 <= SMEM_BYTES, "");
constexpr int B_EMPTYR = 0  , B_SIG = 6  ,
              B_EMPTYA = 20  , B_PEER = 32  , B_PREPD = 34, B_CSD = 35,
              B_KV = 40  , B_XR = 44, B_TAP = 45  , B_CS = 47, B_GO = 48  ,
              B_U = 50  , B_RECV = 54  , B_STX = 56  , B_XT = 58  , B_FULLA = 60  , B_CW = 76,
              B_FULLR = 14  ;
constexpr int B_SIGX = B_SIG, B_SIGE = B_SIG + 1, B_SIGH = B_SIG + 3;

__device__ __forceinline__ uint32_t s2u(const void* p) { return (uint32_t)__cvta_generic_to_shared(p); }
__device__ __forceinline__ void mbar_init(uint32_t b, int n) { asm volatile("mbarrier.init.shared::cta.b64 [%0], %1;" :: "r"(b), "r"(n) : "memory"); }
__device__ __forceinline__ void mbar_expect(uint32_t b, int bytes) { asm volatile("mbarrier.arrive.expect_tx.shared::cta.b64 _, [%0], %1;" :: "r"(b), "r"(bytes) : "memory"); }
__device__ __forceinline__ void mbar_arrive(uint32_t b) { asm volatile("mbarrier.arrive.shared::cta.b64 _, [%0];" :: "r"(b) : "memory"); }
#define MBAR_WAIT_ASM(SEM) \
  asm volatile("{\n .reg .pred p;\nSPIN:\n mbarrier.try_wait.parity" SEM ".shared::cta.b64 p, [%0], %1;\n @!p bra SPIN;\n}" :: "r"(b), "r"(par) : "memory")
__device__ __forceinline__ void mbar_wait(uint32_t b, int par) { MBAR_WAIT_ASM(""); }
__device__ __forceinline__ void mbar_wait_cluster(uint32_t b, int par) {
  MBAR_WAIT_ASM(".relaxed.cluster");
  asm volatile("fence.acquire.sync_restrict::shared::cluster.cluster;" ::: "memory");
}
__device__ __forceinline__ void mbar_wait_bounded(uint32_t b, int par) {
  asm volatile("{\n .reg .pred p, t; .reg .u32 c;\n mov.u32 c, 0;\n"
    "SPIN:\n mbarrier.try_wait.parity.shared::cta.b64 p, [%0], %1;\n @p bra DONE;\n"
    " add.u32 c, c, 1;\n setp.lt.u32 t, c, 1048576;\n @t bra SPIN;\n trap;\nDONE:\n}" :: "r"(b), "r"(par) : "memory");
}
__device__ __forceinline__ uint32_t mapa(uint32_t a, int r) { uint32_t d; asm("mapa.shared::cluster.u32 %0, %1, %2;" : "=r"(d) : "r"(a), "r"(r)); return d; }
__device__ __forceinline__ void st_async4(uint32_t a, uint32_t x, uint32_t y, uint32_t z, uint32_t w, uint32_t bar) {
  asm volatile("st.async.weak.shared::cluster.mbarrier::complete_tx::bytes.v4.b32 [%0], {%1,%2,%3,%4}, [%5];" :: "r"(a), "r"(x), "r"(y), "r"(z), "r"(w), "r"(bar) : "memory");
}
__device__ __forceinline__ void tma3d(uint32_t dst, const CUtensorMap* tm, int c0, int c1, int c2, uint32_t bar) {
  asm volatile("cp.async.bulk.tensor.3d.shared::cluster.global.mbarrier::complete_tx::bytes [%0], [%1, {%3, %4, %5}], [%2];" :: "r"(dst), "l"(tm), "r"(bar), "r"(c0), "r"(c1), "r"(c2) : "memory");
}
__device__ __forceinline__ void sts64(uint32_t a, uint32_t x, uint32_t y) { asm volatile("st.shared.v2.b32 [%0], {%1,%2};" :: "r"(a), "r"(x), "r"(y) : "memory"); }
__device__ __forceinline__ bool elect() { uint32_t p; asm volatile("{ .reg .pred P; elect.sync _|P, 0xffffffff; selp.u32 %0, 1, 0, P; }" : "=r"(p)); return p; }
__device__ __forceinline__ void bulk_ld(uint32_t dst, const void* src, int bytes, uint32_t bar) {
  asm volatile("cp.async.bulk.shared::cluster.global.mbarrier::complete_tx::bytes [%0], [%1], %2, [%3];" :: "r"(dst), "l"(src), "r"(bytes), "r"(bar) : "memory");
}
__device__ __forceinline__ void tma2d(uint32_t dst, const CUtensorMap* tm, int c0, int c1, uint32_t bar) {
  asm volatile("cp.async.bulk.tensor.2d.shared::cluster.global.mbarrier::complete_tx::bytes [%0], [%1, {%3, %4}], [%2];" :: "r"(dst), "l"(tm), "r"(bar), "r"(c0), "r"(c1) : "memory");
}
__device__ __forceinline__ void fence_async_g() { asm volatile("fence.proxy.async.global;" ::: "memory"); }
__device__ __forceinline__ void fence_async_s() { asm volatile("fence.proxy.async.shared::cta;" ::: "memory"); }
__device__ __forceinline__ unsigned ld_acq(const unsigned* p) { unsigned v; asm volatile("ld.acquire.gpu.global.u32 %0, [%1];" : "=r"(v) : "l"(p) : "memory"); return v; }
__device__ __forceinline__ void poll_ge(const unsigned* p, unsigned target, bool active) {
  while (true) {
    bool ok = !active || (int)(ld_acq(p) - target) >= 0;
    if (__all_sync(0xffffffffu, ok)) break;
  }
}
__device__ __forceinline__ void poll1(const unsigned* p, unsigned target) { while ((int)(ld_acq(p) - target) < 0) {} }
__device__ __forceinline__ void signal_gpu(unsigned* p) {
  fence_async_g();
  asm volatile("red.release.gpu.global.add.u32 [%0], 1;" :: "l"(p) : "memory");
}
__device__ __forceinline__ void bar_sync(int id, int n) { asm volatile("bar.sync %0, %1;" :: "r"(id), "r"(n) : "memory"); }
__device__ __forceinline__ void bar_arrive(int id, int n) { asm volatile("bar.arrive %0, %1;" :: "r"(id), "r"(n) : "memory"); }
__device__ __forceinline__ uint32_t lds32(uint32_t a) { uint32_t v; asm volatile("ld.shared.b32 %0, [%1];" : "=r"(v) : "r"(a)); return v; }
__device__ __forceinline__ uint2 lds64(uint32_t a) { uint2 v; asm volatile("ld.shared.v2.b32 {%0,%1}, [%2];" : "=r"(v.x), "=r"(v.y) : "r"(a)); return v; }
__device__ __forceinline__ uint4 lds128(uint32_t a) { uint4 v; asm volatile("ld.shared.v4.b32 {%0,%1,%2,%3}, [%4];" : "=r"(v.x), "=r"(v.y), "=r"(v.z), "=r"(v.w) : "r"(a)); return v; }
__device__ __forceinline__ float4 lds128f(uint32_t a) { float4 v; asm volatile("ld.shared.v4.f32 {%0,%1,%2,%3}, [%4];" : "=f"(v.x), "=f"(v.y), "=f"(v.z), "=f"(v.w) : "r"(a)); return v; }
__device__ __forceinline__ void sts32(uint32_t a, uint32_t v) { asm volatile("st.shared.b32 [%0], %1;" :: "r"(a), "r"(v) : "memory"); }
__device__ __forceinline__ void sts128f(uint32_t a, float x, float y, float z, float w) { asm volatile("st.shared.v4.f32 [%0], {%1,%2,%3,%4};" :: "r"(a), "f"(x), "f"(y), "f"(z), "f"(w) : "memory"); }
__device__ __forceinline__ void ldsm4t(uint32_t a, uint32_t& r0, uint32_t& r1, uint32_t& r2, uint32_t& r3) {
  asm volatile("ldmatrix.sync.aligned.m8n8.x4.trans.shared.b16 {%0,%1,%2,%3}, [%4];" : "=r"(r0), "=r"(r1), "=r"(r2), "=r"(r3) : "r"(a));
}
__device__ __forceinline__ void stsm4(uint32_t a, uint32_t r0, uint32_t r1, uint32_t r2, uint32_t r3) {
  asm volatile("stmatrix.sync.aligned.m8n8.x4.shared.b16 [%0], {%1,%2,%3,%4};" :: "r"(a), "r"(r0), "r"(r1), "r"(r2), "r"(r3) : "memory");
}
__device__ __forceinline__ uint32_t bmul(uint32_t a, uint32_t b) { uint32_t d; asm("mul.rn.bf16x2 %0, %1, %2;" : "=r"(d) : "r"(a), "r"(b)); return d; }
__device__ __forceinline__ uint32_t badd(uint32_t a, uint32_t b) { uint32_t d; asm("add.rn.bf16x2 %0, %1, %2;" : "=r"(d) : "r"(a), "r"(b)); return d; }
__device__ __forceinline__ uint32_t bfma(uint32_t a, uint32_t b, uint32_t c) { uint32_t d; asm("fma.rn.bf16x2 %0, %1, %2, %3;" : "=r"(d) : "r"(a), "r"(b), "r"(c)); return d; }
__device__ __forceinline__ float blo(uint32_t v) { return __uint_as_float(v << 16); }
__device__ __forceinline__ float bhi(uint32_t v) { return __uint_as_float(v & 0xffff0000u); }
__device__ __forceinline__ uint32_t pack2(float lo, float hi) { uint32_t d; asm("cvt.rn.bf16x2.f32 %0, %1, %2;" : "=r"(d) : "f"(hi), "f"(lo)); return d; }
__device__ __forceinline__ uint64_t mkdesc(uint32_t addr, uint32_t lbo, uint32_t sbo, int swz) {
  return (uint64_t)((addr & 0x3FFFF) >> 4) | ((uint64_t)(lbo >> 4) << 16) | ((uint64_t)(sbo >> 4) << 32) | ((uint64_t)swz << 62);
}
__device__ __forceinline__ void wg_fence() { asm volatile("wgmma.fence.sync.aligned;" ::: "memory"); }
__device__ __forceinline__ void wg_commit() { asm volatile("wgmma.commit_group.sync.aligned;" ::: "memory"); }
template <int N> __device__ __forceinline__ void wg_wait() { asm volatile("wgmma.wait_group.sync.aligned %0;" :: "n"(N) : "memory"); }
template <int I0, int I1, int N> __device__ __forceinline__ void reg_fence(float (&d)[N]) {
#pragma unroll
  for (int i = I0; i < I1; i++) asm volatile("" : "+f"(d[i]) :: "memory");
}
template <int I0, int I1, int N> __device__ __forceinline__ void reg_rename(float (&d)[N]) {
#pragma unroll
  for (int i = I0; i < I1; i++) { float t; asm volatile("mov.b32 %0, %1;" : "=f"(t) : "f"(d[i]) : "memory"); d[i] = t; }
}
template <int TA, int TB, int SZ>
__device__ __forceinline__ void wgmma_n64(float (&d)[SZ], uint64_t& a, int ai, uint64_t& b, int bi, int sd) {
  asm volatile("{ .reg .pred p; .reg .b32 l0, h0, l1, h1; setp.ne.b32 p, %36, 0;\n"
    "wgmma.mma_async.sync.aligned.m64n64k16.f32.bf16.bf16 {%0, %1, %2, %3, %4, %5, %6, %7, %8, %9, %10, %11, %12, %13, %14, %15, %16, %17, %18, %19, %20, %21, %22, %23, %24, %25, %26, %27, %28, %29, %30, %31}, %32, %33, p, 1, 1, %37, %38;\n"
    "mov.b64 {l0, h0}, %32; add.s32 l0, l0, %34; mov.b64 %32, {l0, h0};\n"
    "mov.b64 {l1, h1}, %33; add.s32 l1, l1, %35; mov.b64 %33, {l1, h1}; }"
    : "+f"(d[0]), "+f"(d[1]), "+f"(d[2]), "+f"(d[3]), "+f"(d[4]), "+f"(d[5]), "+f"(d[6]), "+f"(d[7]), "+f"(d[8]), "+f"(d[9]), "+f"(d[10]), "+f"(d[11]), "+f"(d[12]), "+f"(d[13]), "+f"(d[14]), "+f"(d[15]), "+f"(d[16]), "+f"(d[17]), "+f"(d[18]), "+f"(d[19]), "+f"(d[20]), "+f"(d[21]), "+f"(d[22]), "+f"(d[23]), "+f"(d[24]), "+f"(d[25]), "+f"(d[26]), "+f"(d[27]), "+f"(d[28]), "+f"(d[29]), "+f"(d[30]), "+f"(d[31]), "+l"(a), "+l"(b)
    : "r"(ai), "r"(bi), "r"(sd), "n"(TA), "n"(TB));
}
template <int TA, int TB, int SZ>
__device__ __forceinline__ void wgmma_n96(float (&d)[SZ], uint64_t& a, int ai, uint64_t& b, int bi, int sd) {
  asm volatile("{ .reg .pred p; .reg .b32 l0, h0, l1, h1; setp.ne.b32 p, %52, 0;\n"
    "wgmma.mma_async.sync.aligned.m64n96k16.f32.bf16.bf16 {%0, %1, %2, %3, %4, %5, %6, %7, %8, %9, %10, %11, %12, %13, %14, %15, %16, %17, %18, %19, %20, %21, %22, %23, %24, %25, %26, %27, %28, %29, %30, %31, %32, %33, %34, %35, %36, %37, %38, %39, %40, %41, %42, %43, %44, %45, %46, %47}, %48, %49, p, 1, 1, %53, %54;\n"
    "mov.b64 {l0, h0}, %48; add.s32 l0, l0, %50; mov.b64 %48, {l0, h0};\n"
    "mov.b64 {l1, h1}, %49; add.s32 l1, l1, %51; mov.b64 %49, {l1, h1}; }"
    : "+f"(d[0]), "+f"(d[1]), "+f"(d[2]), "+f"(d[3]), "+f"(d[4]), "+f"(d[5]), "+f"(d[6]), "+f"(d[7]), "+f"(d[8]), "+f"(d[9]), "+f"(d[10]), "+f"(d[11]), "+f"(d[12]), "+f"(d[13]), "+f"(d[14]), "+f"(d[15]), "+f"(d[16]), "+f"(d[17]), "+f"(d[18]), "+f"(d[19]), "+f"(d[20]), "+f"(d[21]), "+f"(d[22]), "+f"(d[23]), "+f"(d[24]), "+f"(d[25]), "+f"(d[26]), "+f"(d[27]), "+f"(d[28]), "+f"(d[29]), "+f"(d[30]), "+f"(d[31]), "+f"(d[32]), "+f"(d[33]), "+f"(d[34]), "+f"(d[35]), "+f"(d[36]), "+f"(d[37]), "+f"(d[38]), "+f"(d[39]), "+f"(d[40]), "+f"(d[41]), "+f"(d[42]), "+f"(d[43]), "+f"(d[44]), "+f"(d[45]), "+f"(d[46]), "+f"(d[47]), "+l"(a), "+l"(b)
    : "r"(ai), "r"(bi), "r"(sd), "n"(TA), "n"(TB));
}
template <int TA, int TB, int SZ>
__device__ __forceinline__ void wgmma_n128(float (&d)[SZ], uint64_t& a, int ai, uint64_t& b, int bi, int sd) {
  asm volatile("{ .reg .pred p; .reg .b32 l0, h0, l1, h1; setp.ne.b32 p, %68, 0;\n"
    "wgmma.mma_async.sync.aligned.m64n128k16.f32.bf16.bf16 {%0, %1, %2, %3, %4, %5, %6, %7, %8, %9, %10, %11, %12, %13, %14, %15, %16, %17, %18, %19, %20, %21, %22, %23, %24, %25, %26, %27, %28, %29, %30, %31, %32, %33, %34, %35, %36, %37, %38, %39, %40, %41, %42, %43, %44, %45, %46, %47, %48, %49, %50, %51, %52, %53, %54, %55, %56, %57, %58, %59, %60, %61, %62, %63}, %64, %65, p, 1, 1, %69, %70;\n"
    "mov.b64 {l0, h0}, %64; add.s32 l0, l0, %66; mov.b64 %64, {l0, h0};\n"
    "mov.b64 {l1, h1}, %65; add.s32 l1, l1, %67; mov.b64 %65, {l1, h1}; }"
    : "+f"(d[0]), "+f"(d[1]), "+f"(d[2]), "+f"(d[3]), "+f"(d[4]), "+f"(d[5]), "+f"(d[6]), "+f"(d[7]), "+f"(d[8]), "+f"(d[9]), "+f"(d[10]), "+f"(d[11]), "+f"(d[12]), "+f"(d[13]), "+f"(d[14]), "+f"(d[15]), "+f"(d[16]), "+f"(d[17]), "+f"(d[18]), "+f"(d[19]), "+f"(d[20]), "+f"(d[21]), "+f"(d[22]), "+f"(d[23]), "+f"(d[24]), "+f"(d[25]), "+f"(d[26]), "+f"(d[27]), "+f"(d[28]), "+f"(d[29]), "+f"(d[30]), "+f"(d[31]), "+f"(d[32]), "+f"(d[33]), "+f"(d[34]), "+f"(d[35]), "+f"(d[36]), "+f"(d[37]), "+f"(d[38]), "+f"(d[39]), "+f"(d[40]), "+f"(d[41]), "+f"(d[42]), "+f"(d[43]), "+f"(d[44]), "+f"(d[45]), "+f"(d[46]), "+f"(d[47]), "+f"(d[48]), "+f"(d[49]), "+f"(d[50]), "+f"(d[51]), "+f"(d[52]), "+f"(d[53]), "+f"(d[54]), "+f"(d[55]), "+f"(d[56]), "+f"(d[57]), "+f"(d[58]), "+f"(d[59]), "+f"(d[60]), "+f"(d[61]), "+f"(d[62]), "+f"(d[63]), "+l"(a), "+l"(b)
    : "r"(ai), "r"(bi), "r"(sd), "n"(TA), "n"(TB));
}
__device__ __forceinline__ void wgmma_rs_n32(float (&d)[64], const uint32_t* a, uint64_t& b, int bi, int sd) {
  asm volatile("{ .reg .pred p; .reg .b32 l0, h0; setp.ne.b32 p, %22, 0;\n"
    "wgmma.mma_async.sync.aligned.m64n32k16.f32.bf16.bf16 {%0, %1, %2, %3, %4, %5, %6, %7, %8, %9, %10, %11, %12, %13, %14, %15}, {%17, %18, %19, %20}, %16, p, 1, 1, 0;\n"
    "mov.b64 {l0, h0}, %16; add.s32 l0, l0, %21; mov.b64 %16, {l0, h0}; }"
    : "+f"(d[48]), "+f"(d[49]), "+f"(d[50]), "+f"(d[51]), "+f"(d[52]), "+f"(d[53]), "+f"(d[54]), "+f"(d[55]), "+f"(d[56]), "+f"(d[57]), "+f"(d[58]), "+f"(d[59]), "+f"(d[60]), "+f"(d[61]), "+f"(d[62]), "+f"(d[63]), "+l"(b)
    : "r"(a[0]), "r"(a[1]), "r"(a[2]), "r"(a[3]), "r"(bi), "r"(sd));
}
__device__ __forceinline__ void wgmma_rs_n64(float (&d)[64], const uint32_t* a, uint64_t& b, int bi, int sd) {
  asm volatile("{ .reg .pred p; .reg .b32 l0, h0; setp.ne.b32 p, %38, 0;\n"
    "wgmma.mma_async.sync.aligned.m64n64k16.f32.bf16.bf16 {%0, %1, %2, %3, %4, %5, %6, %7, %8, %9, %10, %11, %12, %13, %14, %15, %16, %17, %18, %19, %20, %21, %22, %23, %24, %25, %26, %27, %28, %29, %30, %31}, {%33, %34, %35, %36}, %32, p, 1, 1, 0;\n"
    "mov.b64 {l0, h0}, %32; add.s32 l0, l0, %37; mov.b64 %32, {l0, h0}; }"
    : "+f"(d[32]), "+f"(d[33]), "+f"(d[34]), "+f"(d[35]), "+f"(d[36]), "+f"(d[37]), "+f"(d[38]), "+f"(d[39]), "+f"(d[40]), "+f"(d[41]), "+f"(d[42]), "+f"(d[43]), "+f"(d[44]), "+f"(d[45]), "+f"(d[46]), "+f"(d[47]), "+f"(d[48]), "+f"(d[49]), "+f"(d[50]), "+f"(d[51]), "+f"(d[52]), "+f"(d[53]), "+f"(d[54]), "+f"(d[55]), "+f"(d[56]), "+f"(d[57]), "+f"(d[58]), "+f"(d[59]), "+f"(d[60]), "+f"(d[61]), "+f"(d[62]), "+f"(d[63]), "+l"(b)
    : "r"(a[0]), "r"(a[1]), "r"(a[2]), "r"(a[3]), "r"(bi), "r"(sd));
}
__device__ __forceinline__ void wgmma_rs_n96(float (&d)[64], const uint32_t* a, uint64_t& b, int bi, int sd) {
  asm volatile("{ .reg .pred p; .reg .b32 l0, h0; setp.ne.b32 p, %54, 0;\n"
    "wgmma.mma_async.sync.aligned.m64n96k16.f32.bf16.bf16 {%0, %1, %2, %3, %4, %5, %6, %7, %8, %9, %10, %11, %12, %13, %14, %15, %16, %17, %18, %19, %20, %21, %22, %23, %24, %25, %26, %27, %28, %29, %30, %31, %32, %33, %34, %35, %36, %37, %38, %39, %40, %41, %42, %43, %44, %45, %46, %47}, {%49, %50, %51, %52}, %48, p, 1, 1, 0;\n"
    "mov.b64 {l0, h0}, %48; add.s32 l0, l0, %53; mov.b64 %48, {l0, h0}; }"
    : "+f"(d[16]), "+f"(d[17]), "+f"(d[18]), "+f"(d[19]), "+f"(d[20]), "+f"(d[21]), "+f"(d[22]), "+f"(d[23]), "+f"(d[24]), "+f"(d[25]), "+f"(d[26]), "+f"(d[27]), "+f"(d[28]), "+f"(d[29]), "+f"(d[30]), "+f"(d[31]), "+f"(d[32]), "+f"(d[33]), "+f"(d[34]), "+f"(d[35]), "+f"(d[36]), "+f"(d[37]), "+f"(d[38]), "+f"(d[39]), "+f"(d[40]), "+f"(d[41]), "+f"(d[42]), "+f"(d[43]), "+f"(d[44]), "+f"(d[45]), "+f"(d[46]), "+f"(d[47]), "+f"(d[48]), "+f"(d[49]), "+f"(d[50]), "+f"(d[51]), "+f"(d[52]), "+f"(d[53]), "+f"(d[54]), "+f"(d[55]), "+f"(d[56]), "+f"(d[57]), "+f"(d[58]), "+f"(d[59]), "+f"(d[60]), "+f"(d[61]), "+f"(d[62]), "+f"(d[63]), "+l"(b)
    : "r"(a[0]), "r"(a[1]), "r"(a[2]), "r"(a[3]), "r"(bi), "r"(sd));
}
__device__ __forceinline__ void wgmma_rs_n128(float (&d)[64], const uint32_t* a, uint64_t& b, int bi, int sd) {
  asm volatile("{ .reg .pred p; .reg .b32 l0, h0; setp.ne.b32 p, %70, 0;\n"
    "wgmma.mma_async.sync.aligned.m64n128k16.f32.bf16.bf16 {%0, %1, %2, %3, %4, %5, %6, %7, %8, %9, %10, %11, %12, %13, %14, %15, %16, %17, %18, %19, %20, %21, %22, %23, %24, %25, %26, %27, %28, %29, %30, %31, %32, %33, %34, %35, %36, %37, %38, %39, %40, %41, %42, %43, %44, %45, %46, %47, %48, %49, %50, %51, %52, %53, %54, %55, %56, %57, %58, %59, %60, %61, %62, %63}, {%65, %66, %67, %68}, %64, p, 1, 1, 0;\n"
    "mov.b64 {l0, h0}, %64; add.s32 l0, l0, %69; mov.b64 %64, {l0, h0}; }"
    : "+f"(d[0]), "+f"(d[1]), "+f"(d[2]), "+f"(d[3]), "+f"(d[4]), "+f"(d[5]), "+f"(d[6]), "+f"(d[7]), "+f"(d[8]), "+f"(d[9]), "+f"(d[10]), "+f"(d[11]), "+f"(d[12]), "+f"(d[13]), "+f"(d[14]), "+f"(d[15]), "+f"(d[16]), "+f"(d[17]), "+f"(d[18]), "+f"(d[19]), "+f"(d[20]), "+f"(d[21]), "+f"(d[22]), "+f"(d[23]), "+f"(d[24]), "+f"(d[25]), "+f"(d[26]), "+f"(d[27]), "+f"(d[28]), "+f"(d[29]), "+f"(d[30]), "+f"(d[31]), "+f"(d[32]), "+f"(d[33]), "+f"(d[34]), "+f"(d[35]), "+f"(d[36]), "+f"(d[37]), "+f"(d[38]), "+f"(d[39]), "+f"(d[40]), "+f"(d[41]), "+f"(d[42]), "+f"(d[43]), "+f"(d[44]), "+f"(d[45]), "+f"(d[46]), "+f"(d[47]), "+f"(d[48]), "+f"(d[49]), "+f"(d[50]), "+f"(d[51]), "+f"(d[52]), "+f"(d[53]), "+f"(d[54]), "+f"(d[55]), "+f"(d[56]), "+f"(d[57]), "+f"(d[58]), "+f"(d[59]), "+f"(d[60]), "+f"(d[61]), "+f"(d[62]), "+f"(d[63]), "+l"(b)
    : "r"(a[0]), "r"(a[1]), "r"(a[2]), "r"(a[3]), "r"(bi), "r"(sd));
}

__device__ __forceinline__ void prep_task(uint32_t src, uint32_t dst, uint32_t bar, uint32_t w0, uint32_t w1, uint32_t w2, uint32_t w3) {
  uint32_t k[12], u[9];
#pragma unroll
  for (int j = 0; j < 12; j++) k[j] = lds32(j < 4 ? src + (4 + j) * 528 - 16 : src + (j - 4) * 528);
#pragma unroll
  for (int j = 0; j < 9; j++) u[j] = lds32(j < 1 ? src + 4224 + 7 * 528 - 16 : src + 4224 + (j - 1) * 528);
#pragma unroll
  for (int j = 0; j < 9; j++) {
    uint32_t s = bmul(k[j], w3);
    s = badd(s, bmul(k[j + 1], w2));
    s = badd(s, bmul(k[j + 2], w1));
    s = badd(s, bmul(k[j + 3], w0));
    u[j] = bmul(s, u[j]);
  }
#pragma unroll
  for (int c = 0; c < 2; c++) {
    const uint32_t sel = c ? 0x7632 : 0x5410;
    st_async4(dst + c * U_PITCH, __byte_perm(u[2], u[1], sel), __byte_perm(u[4], u[3], sel), __byte_perm(u[6], u[5], sel), __byte_perm(u[8], u[7], sel), bar);
    st_async4(dst + c * U_PITCH + U_ODD, __byte_perm(u[1], u[0], sel), __byte_perm(u[3], u[2], sel), __byte_perm(u[5], u[4], sel), __byte_perm(u[7], u[6], sel), bar);
  }
}

template <int S, int C0, int NK>
__device__ __forceinline__ void frag_load(uint32_t (&P)[4 * NK], uint32_t ua, uint32_t z) {
  P[2] = lds32(ua + 1024 * S + 32 * C0 - 16);
#pragma unroll
  for (int kk = 0; kk < NK; kk++) { P[4 * kk] = lds32(ua + 1024 * S + 32 * (C0 + kk)); P[4 * kk + 1] = lds32(ua + 1024 * S + 32 * (C0 + kk) + 16); }
#pragma unroll
  for (int kk = 0; kk < NK; kk++) { P[4 * kk + 3] = P[4 * kk] ^ z; if (kk) P[4 * kk + 2] = P[4 * kk - 3] ^ z; }
#pragma unroll
  for (int i = 0; i < 4 * NK; i++) asm volatile("" : "+r"(P[i]) :: "memory");
}
template <int S, int C0, int NK, int CH>
__device__ __forceinline__ void conv_issue(float (&acc)[64], const uint32_t (&P)[4 * NK], uint64_t& db, int im1) {
  if (S > 0 && C0 == 0) reg_rename<16 * S, 64>(acc);
  wg_fence();
#pragma unroll
  for (int kk = 0; kk < NK; kk++) {
    const int inc = C0 + kk < 7 ? im1 : 14 + (CH ? -1 : 1) * (int)(T_PITCH / 8);
    if (S == 0) wgmma_rs_n128(acc, &P[4 * kk], db, inc, C0 + kk != 0);
    if (S == 1) wgmma_rs_n96(acc, &P[4 * kk], db, inc, 1);
    if (S == 2) wgmma_rs_n64(acc, &P[4 * kk], db, inc, 1);
    if (S == 3) wgmma_rs_n32(acc, &P[4 * kk], db, inc, 1);
  }
  wg_commit();
}
template <int S>
__device__ __forceinline__ void conv_dump(float (&acc)[64], uint32_t xw, int wl) {
  reg_fence<16 * S, 16 * S + 16>(acc);
#pragma unroll
  for (int r = 0; r < 3; r++) {
    const int i = 16 * S + 4 * (r + 1);
    if (S < 3 || wl + r + 1 < 4) sts64(xw + (4 * S + r + 1) * 768 + r * 256, pack2(acc[i], acc[i + 1]), pack2(acc[i + 2], acc[i + 3]));
  }
}
template <int S>
__device__ __forceinline__ void conv_reduce(float (&y)[4], const float (&acc)[64], uint32_t xw, int wl) {
#pragma unroll
  for (int i = 0; i < 4; i++) y[i] = acc[16 * S + i];
#pragma unroll
  for (int r = 0; r < 3; r++) {
    uint2 v = make_uint2(0u, 0u);
    if (S > 0 || r < wl) v = lds64(xw + 4 * S * 768 + r * 256);
    y[0] += blo(v.x); y[1] += bhi(v.x); y[2] += blo(v.y); y[3] += bhi(v.y);
  }
}
struct FinCtx { uint32_t um, xt, st, DA, DB; uint32_t *hA, *hB; };
template <int S>
__device__ __forceinline__ void conv_z(uint32_t (&zz)[4], const FinCtx& c, const float (&aA)[64], const float (&aB)[64], uint32_t xA, uint32_t xB, int wl) {
  uint32_t u[4];
  float ya[4], yb[4];
  ldsm4t(c.um + S * 1024, u[0], u[1], u[2], u[3]);
  conv_reduce<S>(ya, aA, xA, wl); conv_reduce<S>(yb, aB, xB, wl);
  zz[0] = bfma(u[0], c.DA, pack2(ya[0], ya[1])); zz[1] = bfma(u[1], c.DA, pack2(ya[2], ya[3]));
  zz[2] = bfma(u[2], c.DB, pack2(yb[0], yb[1])); zz[3] = bfma(u[3], c.DB, pack2(yb[2], yb[3]));
}
template <int S>
__device__ __forceinline__ void conv_fin(const FinCtx& c, const uint32_t (&zz)[4]) {
  constexpr uint32_t XO = (S < 2 ? OFF_XTE : OFF_XTL) + (S & 1) * 4096, SO = (S < 2 ? OFF_STE : OFF_STL) + (S & 1) * 2048;
#pragma unroll
  for (int h = 0; h < 2; h++) {
    uint2 sv = lds64(c.st + SO + h * 256);
    uint32_t xa = lds32(c.xt + XO + h * 512), xb = lds32((c.xt ^ 64) + XO + h * 512);
    c.hA[(8 * S + h) * (D_ * 32)] = bfma(bfma(xa, sv.x, sv.y), zz[h], xa);
    c.hB[(8 * S + h) * (D_ * 32)] = bfma(bfma(xb, sv.x, sv.y), zz[2 + h], xb);
  }
}

struct RowC { float nm, k1, k2, hs; };
__device__ __forceinline__ float geglu(float g, float u, float cg, float cu, const RowC& r) {
  float gc = fmaf(r.nm, cg, g), uc = fmaf(r.nm, cu, u);
  float in = gc * fmaf(gc * gc, r.k2, r.k1);
  float t; asm("tanh.approx.f32 %0, %1;" : "=f"(t) : "f"(in));
  float pr = gc * uc;
  return fmaf(pr, t, pr);
}
template <int GI, int UI, int N>
__device__ __forceinline__ void epi_group(const float (&acc)[N], uint32_t cs, const RowC& r0, const RowC& r1, uint32_t* dst) {
  float4 c = lds128f(cs);
  uint32_t lo = pack2(geglu(acc[GI], acc[UI], c.x, c.z, r0), geglu(acc[GI + 1], acc[UI + 1], c.y, c.w, r0));
  uint32_t hi = pack2(geglu(acc[GI + 2], acc[UI + 2], c.x, c.z, r1), geglu(acc[GI + 3], acc[UI + 3], c.y, c.w, r1));
  dst[0] = lo; dst[32] = hi;
}

struct Params {
  const uint16_t *x, *shift_k, *ssm_k, *ssm_D, *wg, *wu, *wd;
  uint16_t* out;
  Scratch* scr;
  int i128, i64, im1;
  uint64_t z64;
};

__global__ void __launch_bounds__(NTHR, 1)
fused_kernel(const Params p, const __grid_constant__ CUtensorMap tmK, const __grid_constant__ CUtensorMap tmV,
             const __grid_constant__ CUtensorMap tmG, const __grid_constant__ CUtensorMap tmU,
             const __grid_constant__ CUtensorMap tmG32, const __grid_constant__ CUtensorMap tmU32,
             const __grid_constant__ CUtensorMap tmD, const __grid_constant__ CUtensorMap tmX, const __grid_constant__ CUtensorMap tmT) {
  extern __shared__ __align__(1024) uint8_t smem[];
  const uint32_t sb = s2u(smem);
  const int tid = threadIdx.x, lane = tid & 31;
  const int warp = __shfl_sync(0xffffffffu, tid >> 5, 0);
  const int rank = blockIdx.x & 1, cl = blockIdx.x >> 1;
  const int pair = cl < 4 ? cl : cl < 36 ? 4 + ((cl - 4) & 7) * 4 + ((cl - 4) >> 3) : 36 + ((cl - 36) % 7) * 4 + (cl - 36) / 7;
  const int bid = pair * 2 + rank;
  const int tile = bid >> 3, js = bid & 7;
  const int g = lane >> 2, q = lane & 3;
  auto BAR = [&](int i) { return sb + OFF_BAR + i * 8; };
  auto kv_load = [&](int pc) {
    uint32_t b = BAR(B_KV + pc), d = sb + OFF_KV + pc * KV_PIECE;
    int run0 = pc * 64 + rank * 32 - 1;
    mbar_expect(b, KV_PIECE);
    tma3d(d, &tmK, pair * 8, run0, 0, b);
    tma3d(d + 4224, &tmV, pair * 8, run0, 0, b);
  };
  uint4 small;
  if (warp >= 8) {
    if (elect()) {
      const int cnt = warp < 10 ? 8 : (warp < 12 ? 4 : 1);
#pragma unroll
      for (int i = 0; i < 10; i++) mbar_init(BAR((warp - 8) * 10 + i), i >= 4 && warp == 9 ? 1 : cnt);
      asm volatile("fence.mbarrier_init.release.cluster;" ::: "memory");
      if (warp == 12) {
        const uint16_t* xs = p.x + (size_t)(tok(bid >> 2, (bid & 3) * 16 + 8)) * D_;
        mbar_expect(BAR(B_XR), 16384);
#pragma unroll
        for (int n = 0; n < 8; n++) bulk_ld(sb + OFF_XR + n * 2064, xs + n * 16 * D_, 2048, BAR(B_XR));
        kv_load(0);
#pragma unroll
        for (int i = 0; i < 2; i++) {
          mbar_expect(BAR(B_TAP + i), 2 * T_PITCH);
          tma3d(sb + OFF_TAP + i * 2 * T_PITCH, &tmT, 0, -8, bid * 4 + 2 * i, BAR(B_TAP + i));
        }
        SSTAMP(true, 26);
      }
      if (warp == 13) {
#pragma unroll
        for (int i = 0; i < 8; i++) mbar_expect(BAR(B_U + i), i < 4 ? 8192 : i < 6 ? 16384 : 512);
      }
    }
    __syncwarp();
    if (warp < 12) small = __ldg((const uint4*)(p.shift_k + (pair * 8 + 2 * q) * 4));
    else small.x = p.scr->epoch[bid];
  } else {
    const uint2 d4 = __ldg((const uint2*)(p.ssm_D + bid * 4));
    small.x = d4.x; small.y = d4.y;
    if (tid < 64) sts32(sb + OFF_U + (tid >> 4) * U_PITCH + ((tid >> 3) & 1) * U_ODD + (tid & 7) * 4, 0u);
  }
  __syncthreads();
  asm volatile("barrier.cluster.arrive.relaxed.aligned;" ::: "memory");
  SSTAMP(tid == 0, 13);

  if (warp < 8) {
    asm volatile("setmaxnreg.inc.sync.aligned.u32 208;");
    {
      mbar_wait(BAR(B_XR), 0);
      SSTAMP(tid == 0, 49);
      const int mi = lane >> 3, rho = lane & 7;
      const int t = (rho & 1) + 4 * (rho >> 1) + 2 * (mi & 1);
      const uint32_t xa = sb + OFF_XR + (t & 7) * 2064 + ((t >> 3) ^ 1) * 1024 + (mi >> 1) * 16 + warp * 128;
      const uint32_t xo = sb + OFF_XST + warp * 2048 + (g ^ (bid & 3)) * 32 + q * 8;
#pragma unroll
      for (int i = 0; i < 4; i++) {
        uint32_t m0, m1, m2, m3;
        ldsm4t(xa + i * 32, m0, m1, m2, m3);
        sts64(xo + i * 512, m0, m1);
        sts64(xo + i * 512 + 256, m2, m3);
      }
      const int r = tid >> 4;
      const uint32_t ra = sb + OFF_XR + (r & 7) * 2064 + ((r >> 3) ^ 1) * 1024 + (tid & 15) * 16;
      float f[32];
#pragma unroll
      for (int i = 0; i < 4; i++) {
        uint4 v = lds128(ra + i * 256);
        f[8 * i] = blo(v.x); f[8 * i + 1] = bhi(v.x); f[8 * i + 2] = blo(v.y); f[8 * i + 3] = bhi(v.y);
        f[8 * i + 4] = blo(v.z); f[8 * i + 5] = bhi(v.z); f[8 * i + 6] = blo(v.w); f[8 * i + 7] = bhi(v.w);
      }
      float sa = 0.f, sc = 0.f;
#pragma unroll
      for (int i = 0; i < 16; i++) { sa += f[2 * i]; sc += f[2 * i + 1]; }
      sa += sc;
#pragma unroll
      for (int o = 1; o < 16; o <<= 1) sa += __shfl_xor_sync(0xffffffffu, sa, o);
      const float mean = sa * (1.f / D_);
      float qa = 0.f, qc = 0.f;
#pragma unroll
      for (int i = 0; i < 16; i++) { float d0 = f[2 * i] - mean, d1 = f[2 * i + 1] - mean; qa = fmaf(d0, d0, qa); qc = fmaf(d1, d1, qc); }
      qa += qc;
#pragma unroll
      for (int o = 1; o < 16; o <<= 1) qa += __shfl_xor_sync(0xffffffffu, qa, o);
      const float rs = blo(pack2(rsqrtf(fmaf(qa, 1.f / D_, 1e-5f)), 0.f));
      const uint32_t me = pack2(rs, -mean * rs), ot = __shfl_xor_sync(0xffffffffu, me, 16);
      if (lane == 0) sts64(sb + OFF_CS + warp * 8, __byte_perm(me, ot, 0x5410), __byte_perm(me, ot, 0x7632));
      __syncwarp();
      if (lane == 0) mbar_arrive(BAR(B_SIGX));
      SSTAMP(tid == 0, 48);
    }
    const int hw = warp >> 2, wl = warp & 3;
    {
      const int chA = bid * 4 + hw, chB = chA + 2;
      const int ig = g ^ 1;
      const uint32_t uA = sb + OFF_U + hw * U_PITCH + ((ig & 1) ? 0 : U_ODD) + 32 + ((ig - 2 * q) >> 1) * 4 + wl * 256;
      const uint32_t uB = uA + 2 * U_PITCH;
      uint64_t dT = (mkdesc(sb + OFF_TAP + hw * T_PITCH + 256, 16, 256, 3) + p.z64);
      const uint32_t z = blockIdx.x >> 16;
      const int im1 = p.im1 ^ z;
      const uint32_t xA = sb + OFF_XCH + (hw * 32 + wl) * 768 + lane * 8, xB = xA + 16 * 768;
      FinCtx fc;
      fc.um = sb + OFF_U + (hw + 2 * (lane >> 4)) * U_PITCH + 32 + wl * 256 + (lane & 7) * 32 + ((lane >> 3) & 1) * 16;
      fc.xt = sb + wl * 1024 + (lane >> 3) * 128 + (hw ^ (lane >> 3)) * 32 + (lane & 7) * 4;
      fc.st = sb + wl * 512 + lane * 8;
      fc.DA = __byte_perm(small.x, 0, hw ? 0x3232 : 0x1010); fc.DB = __byte_perm(small.y, 0, hw ? 0x3232 : 0x1010);
      fc.hA = (uint32_t*)p.scr->hT + (size_t)wl * 2 * (D_ * 32) + chA * 32 + ((g ^ (chA & 7)) * 4) + q;
      fc.hB = (uint32_t*)p.scr->hT + (size_t)wl * 2 * (D_ * 32) + chB * 32 + ((g ^ (chB & 7)) * 4) + q;
      asm volatile("barrier.cluster.wait.aligned;" ::: "memory");
      mbar_wait(BAR(B_TAP), 0);
      SSTAMP(tid == 0, 2);
      float aA[64], aB[64];
      uint32_t z0[4], z1[4];
      {
        uint32_t P[16], Q[16];
        mbar_wait_cluster(BAR(B_U + 0), 0);
        SSTAMP(tid == 0, 3);
        frag_load<0, 0, 4>(P, uA, z); conv_issue<0, 0, 4, 0>(aA, P, dT, im1);
        frag_load<0, 4, 4>(Q, uA, z); conv_issue<0, 4, 4, 0>(aA, Q, dT, im1);
        mbar_wait(BAR(B_TAP + 1), 0);
        wg_wait<1>(); frag_load<0, 0, 4>(P, uB, z); conv_issue<0, 0, 4, 1>(aB, P, dT, im1);
        wg_wait<1>(); frag_load<0, 4, 4>(Q, uB, z); conv_issue<0, 4, 4, 1>(aB, Q, dT, im1);
        conv_dump<0>(aA, xA, wl);
        SSTAMP(tid == 0, 4);
        mbar_wait_cluster(BAR(B_U + 1), 0);
        SSTAMP(tid == 0, 5);
        wg_wait<1>(); frag_load<1, 0, 4>(P, uA, z); conv_issue<1, 0, 4, 0>(aA, P, dT, im1);
        wg_wait<1>(); frag_load<1, 4, 4>(Q, uA, z); conv_issue<1, 4, 4, 0>(aA, Q, dT, im1);
        conv_dump<0>(aB, xB, wl);
        wg_wait<1>(); frag_load<1, 0, 4>(P, uB, z); conv_issue<1, 0, 4, 1>(aB, P, dT, im1);
        bar_sync(1 + hw, 128);
        conv_z<0>(z0, fc, aA, aB, xA, xB, wl);
        wg_wait<1>(); frag_load<1, 4, 4>(Q, uB, z); conv_issue<1, 4, 4, 1>(aB, Q, dT, im1);
        conv_dump<1>(aA, xA, wl);
      }
      {
        uint32_t P[32], Q[32];
        SSTAMP(tid == 0, 6);
        mbar_wait_cluster(BAR(B_U + 2), 0);
        wg_wait<1>(); frag_load<2, 0, 8>(P, uA, z); conv_issue<2, 0, 8, 0>(aA, P, dT, im1);
        wg_wait<1>(); frag_load<2, 0, 8>(Q, uB, z); conv_issue<2, 0, 8, 1>(aB, Q, dT, im1);
        conv_dump<1>(aB, xB, wl);
        bar_sync(1 + hw, 128);
        conv_z<1>(z1, fc, aA, aB, xA, xB, wl);
        SSTAMP(tid == 0, 1);
        mbar_wait(BAR(B_XT), 0);
        SSTAMP(tid == 0, 7);
        conv_fin<0>(fc, z0);
        conv_fin<1>(fc, z1);
        __syncwarp();
        if (lane == 0) mbar_arrive(BAR(B_SIGE + 0));
        SSTAMP(tid == 0, 8);
        mbar_wait_cluster(BAR(B_U + 3), 0);
        wg_wait<1>(); frag_load<3, 0, 8>(P, uA, z); conv_issue<3, 0, 8, 0>(aA, P, dT, im1);
        wg_wait<1>(); frag_load<3, 0, 8>(Q, uB, z); conv_issue<3, 0, 8, 1>(aB, Q, dT, im1);
        SSTAMP(tid == 0, 9);
        conv_dump<2>(aA, xA, wl); conv_dump<2>(aB, xB, wl);
        wg_wait<0>();
        conv_dump<3>(aA, xA, wl); conv_dump<3>(aB, xB, wl);
        SSTAMP(tid == 0, 10);
        bar_sync(1 + hw, 128);
        mbar_wait(BAR(B_XT + 1), 0);
        SSTAMP(tid == 0, 11);
        conv_z<2>(z0, fc, aA, aB, xA, xB, wl);
        conv_fin<2>(fc, z0);
        conv_z<3>(z1, fc, aA, aB, xA, xB, wl);
        conv_fin<3>(fc, z1);
        __syncwarp();
        if (lane == 0) mbar_arrive(BAR(B_SIGE + 1));
        STAMP_IF(tid == 0, 12);
      }
    }
    const int blk = tile + 16 * hw;
    const uint32_t aw = sb + OFF_A + hw * 65536;
    const uint32_t fullA = BAR(B_FULLA + hw * 8), emptyA = BAR(B_EMPTYA + hw * 6);
    const uint32_t lmo = aw + (((lane >> 4) * 8 + (lane & 7)) * 128) + (((2 * wl + ((lane >> 3) & 1)) ^ (lane & 7)) * 16);
    uint64_t da = (mkdesc(aw, 0, 1024, 1) + p.z64), db = (mkdesc(sb + OFF_RING, 8192, 1024, 1) + p.z64);
    float acc1[64], acc2[64];
    RowC r0, r1;
    const int TS = 16 + hw * 16; (void)TS;

    {
      int slot = 0;
#pragma unroll 1
      for (int s = 0; s < 8; s++) {
        TW(twa, mbar_wait(fullA + s * 8, 0));
        STAMP_IF(wl == 0 && lane == 0 && s == 0, TS + 0);
        TW(twr, mbar_wait(BAR(B_FULLR + slot), s >= 6));
        wg_fence();
#pragma unroll
        for (int kk = 0; kk < 4; kk++) wgmma_n128<1, 1>(acc1, da, p.i128, db, kk < 3 ? p.i128 : (slot == 5 ? 640 - 6144 : 640), (s | kk) != 0);
        wg_commit();
        TW(twg, wg_wait<1>());
        if (lane == 0 && s > 0) mbar_arrive(BAR(B_EMPTYR + (slot == 0 ? 5 : slot - 1)));
        slot = slot == 5 ? 0 : slot + 1;
      }
    }
    STAMP_IF(wl == 0 && lane == 0, TS + 1);
    TWOUT(tid == 128, 1, twa); TWOUT(tid == 128, 2, twr); TWOUT(tid == 128, 3, twg);
    uint32_t* hdst = (uint32_t*)p.scr->H + (size_t)blk * (86 * 512) + wl * 64 + lane;
    const uint32_t csa = sb + OFF_CS + q * 16;
    da -= 4096;
#pragma unroll
    for (int s = 0; s < 8; s++) {
      constexpr int R0 = 8;
      const int r = R0 + s, slot = r % 6;
      TW(twr, mbar_wait(BAR(B_FULLR + slot), (r / 6) & 1));
      wg_fence();
#pragma unroll
      for (int kk = 0; kk < 4; kk++) wgmma_n128<1, 1>(acc2, da, s == 7 && kk == 3 ? 128 - 4096 : p.i128, db, kk < 3 ? p.i128 : (slot == 5 ? 640 - 6144 : 640), (s | kk) != 0);
      wg_commit();
      uint32_t* d = hdst + js * 8 * 256;
      if (s == 1) {
        reg_fence<0, 64>(acc1);
        TW(twa, mbar_wait_cluster(BAR(B_STX + hw), 0));
        auto mk = [](uint2 v) {
          const float rs = __uint_as_float(v.y), r2 = rs * rs;
          RowC r; r.nm = __uint_as_float(v.x); r.k1 = 0.7978845608028654f * rs; r.k2 = 0.044715f * r2 * r.k1; r.hs = 0.5f * r2;
          return r;
        };
        r0 = mk(lds64(sb + OFF_STX + warp * 128 + g * 8)); r1 = mk(lds64(sb + OFF_STX + warp * 128 + 64 + g * 8));
        TW(twa, mbar_wait(BAR(B_CS), 0));
        epi_group<0, 32>(acc1, csa + 0 * 64, r0, r1, d);
        epi_group<4, 36>(acc1, csa + 1 * 64, r0, r1, d + 256);
      }
      if (s == 2) { epi_group<8, 40>(acc1, csa + 2 * 64, r0, r1, d + 512); epi_group<12, 44>(acc1, csa + 3 * 64, r0, r1, d + 768); }
      if (s == 3) { epi_group<16, 48>(acc1, csa + 4 * 64, r0, r1, d + 1024); epi_group<20, 52>(acc1, csa + 5 * 64, r0, r1, d + 1280); }
      if (s == 4) { epi_group<24, 56>(acc1, csa + 6 * 64, r0, r1, d + 1536); epi_group<28, 60>(acc1, csa + 7 * 64, r0, r1, d + 1792);
                    __syncwarp(); if (lane == 0) mbar_arrive(BAR(B_SIGH + 0)); }
      TW(twg, wg_wait<1>());
      if (lane == 0) mbar_arrive(BAR(B_EMPTYR + (r - 1) % 6));
    }
    STAMP_IF(wl == 0 && lane == 0, TS + 2);
    TWOUT(tid == 128, 4, twa); TWOUT(tid == 128, 5, twr); TWOUT(tid == 128, 6, twg);
    db = (mkdesc(sb + OFF_RING + 4 * 16384, 4096, 512, 2) + p.z64);
    float acc3[48];
    uint32_t res[16];
#pragma unroll
    for (int s = 0; s < 8; s++) {
      constexpr int R0 = 16;
      const int r = R0 + s, slot = r % 6;
      TW(twr, mbar_wait(BAR(B_FULLR + slot), (r / 6) & 1));
      wg_fence();
#pragma unroll
      for (int kk = 0; kk < 4; kk++) wgmma_n96<1, 1>(acc3, da, p.i128, db, kk < 3 ? p.i64 : (slot == 5 ? 832 - 6144 : 832), (s | kk) != 0);
      wg_commit();
      uint32_t* d = hdst + (64 + js * 8) * 256;
      if (s == 0) {
#pragma unroll
        for (int kk = 0; kk < 4; kk++) ldsm4t(lmo + js * 8192 + kk * 2048, res[4 * kk], res[4 * kk + 1], res[4 * kk + 2], res[4 * kk + 3]);
        TW(twg, wg_wait<1>());
        if (lane == 0) mbar_arrive(BAR(B_EMPTYR + (r - 1) % 6));
        reg_fence<0, 64>(acc2);
        epi_group<0, 32>(acc2, csa + 8 * 64, r0, r1, d); epi_group<4, 36>(acc2, csa + 9 * 64, r0, r1, d + 256);
      }
      if (s == 1) { epi_group<8, 40>(acc2, csa + 10 * 64, r0, r1, d + 512); epi_group<12, 44>(acc2, csa + 11 * 64, r0, r1, d + 768); }
      if (s == 2) { epi_group<16, 48>(acc2, csa + 12 * 64, r0, r1, d + 1024); epi_group<20, 52>(acc2, csa + 13 * 64, r0, r1, d + 1280); }
      if (s == 3) { epi_group<24, 56>(acc2, csa + 14 * 64, r0, r1, d + 1536); epi_group<28, 60>(acc2, csa + 15 * 64, r0, r1, d + 1792);
                    __syncwarp(); if (lane == 0) mbar_arrive(BAR(B_SIGH + 1)); }
      if (s > 0) {
        TW(twg, wg_wait<1>());
        if (lane == 0) { mbar_arrive(BAR(B_EMPTYR + (r - 1) % 6)); if (s < 7) mbar_arrive(emptyA + (s - 1) * 8); }
      }
    }
    STAMP_IF(wl == 0 && lane == 0, TS + 3);
    TWOUT(tid == 128, 7, twa); TWOUT(tid == 128, 8, twr); TWOUT(tid == 128, 9, twg);
    da = (mkdesc(aw, 1024, 128, 0) + p.z64); db = (mkdesc(sb + OFF_RING, 8192, 1024, 1) + p.z64);
    float acco[64];
    {
      TW(twa, mbar_wait(fullA, 1));
      TW(twr, mbar_wait(BAR(B_FULLR), 0));
      wg_fence();
#pragma unroll
      for (int kk = 0; kk < 4; kk++) wgmma_n128<0, 1>(acco, da, p.i128, db, kk < 3 ? p.i128 : 640, kk != 0);
      wg_commit();
      TW(twg, wg_wait<1>());
      if (lane == 0) {
        mbar_arrive(BAR(B_EMPTYR + 23 % 6));
        asm volatile("mbarrier.arrive.relaxed.cluster.shared::cluster.b64 _, [%0];" :: "r"(mapa(BAR(B_PEER + hw), rank ^ 1)) : "memory");
      }
      reg_fence<0, 48>(acc3);
      uint32_t* d = hdst + (128 + js * 4) * 256;
      uint32_t* dx = hdst + (160 + js * 2) * 256;
      epi_group<0, 16>(acc3, csa + 16 * 64, r0, r1, d); epi_group<4, 20>(acc3, csa + 17 * 64, r0, r1, d + 256);
      epi_group<8, 24>(acc3, csa + 18 * 64, r0, r1, d + 512); epi_group<12, 28>(acc3, csa + 19 * 64, r0, r1, d + 768);
      if (js < 6) { epi_group<32, 40>(acc3, csa + 20 * 64, r0, r1, dx); epi_group<36, 44>(acc3, csa + 21 * 64, r0, r1, dx + 256); }
      __syncwarp();
      if (lane == 0) mbar_arrive(BAR(B_SIGH + 2));
      STAMP_IF(wl == 0 && lane == 0, TS + 4);
      int slot = 1;
#pragma unroll 1
      for (int s = 1; s < 8; s++) {
        TW(twa, mbar_wait(fullA + slot * 8, s < 6));
        TW(twr, mbar_wait(BAR(B_FULLR + slot), s >= 6));
        wg_fence();
#pragma unroll
        for (int kk = 0; kk < 4; kk++)
          wgmma_n128<0, 1>(acco, da, kk < 3 ? p.i128 : (slot == 5 ? 128 - 3072 : 128), db, kk < 3 ? p.i128 : (slot == 5 ? 640 - 6144 : 640), 1);
        wg_commit();
        TW(twg, wg_wait<1>());
        const int ps = slot == 0 ? 5 : slot - 1;
        if (lane == 0) { mbar_arrive(emptyA + ps * 8); mbar_arrive(BAR(B_EMPTYR + ps)); }
        slot = slot == 5 ? 0 : slot + 1;
        STAMP_IF(wl == 0 && lane == 0 && s == 4, TS + 5);
      }
    }
    wg_wait<0>();
    if (lane == 0) mbar_arrive(emptyA + 1 * 8);
    reg_fence<32, 64>(acco);
    reg_rename<0, 32>(acco);
    STAMP_IF(wl == 0 && lane == 0, TS + 6);
    TWOUT(tid == 128, 10, twa); TWOUT(tid == 128, 11, twr); TWOUT(tid == 128, 13, twg);
    {
      mbar_wait_cluster(BAR(B_PEER + hw), 0);
      const uint32_t ra = mapa(aw + 6 * 8192 + wl * 4096 + lane * 16, rank ^ 1), rb = mapa(BAR(B_RECV + hw), rank ^ 1);
#pragma unroll
      for (int s = 8; s < 14; s++) {
        const int slot = s % 6, rs = 2 + ((s - 8) >> 1);
        if (s < 12) {
#pragma unroll
          for (int i = 2 * (s - 8); i < 2 * (s - 8) + 2; i++)
            st_async4(ra + i * 512, __float_as_uint(acco[32 + 4 * i]), __float_as_uint(acco[33 + 4 * i]),
                      __float_as_uint(acco[34 + 4 * i]), __float_as_uint(acco[35 + 4 * i]), rb);
        }
        TW(twa, mbar_wait(fullA + slot * 8, (s / 6 + 1) & 1));
        if ((s & 1) == 0) TW(twr, mbar_wait(BAR(B_FULLR + rs), 1));
        STAMP_IF(wl == 0 && lane == 0 && s == 8, TS + 7);
        wg_fence();
#pragma unroll
        for (int kk = 0; kk < (s == 13 ? 2 : 4); kk++)
          wgmma_n64<0, 1>(acco, da, kk == 3 && slot == 5 ? 128 - 3072 : p.i128, db, p.i128, 1);
        wg_commit();
      }
    }
    {
      mbar_wait_cluster(BAR(B_RECV + hw), 0);
      if (lane == 0) mbar_arrive(BAR(B_SIG + 6));
      STAMP_IF(tid == 0, 0);
      float base[32];
#pragma unroll
      for (int i = 0; i < 8; i++) {
        float4 o = lds128f(aw + 6 * 8192 + wl * 4096 + lane * 16 + i * 512);
        base[4 * i] = fmaf(o.x, r0.hs, blo(res[2 * i])); base[4 * i + 1] = fmaf(o.y, r0.hs, bhi(res[2 * i]));
        base[4 * i + 2] = fmaf(o.z, r1.hs, blo(res[2 * i + 1])); base[4 * i + 3] = fmaf(o.w, r1.hs, bhi(res[2 * i + 1]));
      }
      reg_fence<0, 32>(base);
      wg_wait<0>();
      reg_fence<0, 32>(acco);
      STAMP_IF(wl == 0 && lane == 0, TS + 8);
      TWOUT(tid == 128, 26, twa); TWOUT(tid == 128, 27, twr); TWOUT(tid == 128, 28, twg);
#pragma unroll
      for (int i = 0; i < 32; i++) acco[i] = fmaf(acco[i], (i & 2) ? r1.hs : r0.hs, base[i]);
      __syncwarp();
      const uint32_t ob = aw + 6 * 8192 + wl * 4096;
      const int row = (lane & 7) + ((lane >> 3) & 1) * 8;
#pragma unroll
      for (int i = 0; i < 4; i++) {
        int chunk = 2 * i + (lane >> 4);
        stsm4(ob + row * 128 + ((chunk ^ (row & 7)) * 16),
              pack2(acco[8 * i], acco[8 * i + 1]), pack2(acco[8 * i + 2], acco[8 * i + 3]),
              pack2(acco[8 * i + 4], acco[8 * i + 5]), pack2(acco[8 * i + 6], acco[8 * i + 7]));
      }
      __syncwarp();
#pragma unroll
      for (int i = 0; i < 4; i++) {
        int rr = i * 4 + (lane >> 3);
        uint4 v = lds128(ob + rr * 128 + (((lane & 7) ^ (rr & 7)) * 16));
        *(uint4*)(p.out + (size_t)tok(blk, wl * 16 + rr) * D_ + js * 64 + (lane & 7) * 8) = v;
      }
    }
    STAMP_IF(wl == 0 && lane == 0, TS + 9);
    STAMP_NS(tid == 0, 15);
  } else if (warp < 12) {
    asm volatile("setmaxnreg.dec.sync.aligned.u32 56;");
    const int h = warp - 8;
    const uint4 sk = small;
    const uint32_t w0 = __byte_perm(sk.x, sk.z, 0x5410), w1 = __byte_perm(sk.x, sk.z, 0x7632);
    const uint32_t w2 = __byte_perm(sk.y, sk.w, 0x5410), w3 = __byte_perm(sk.y, sk.w, 0x7632);
    const uint32_t psrc = sb + OFF_KV + 16 + lane * 4 + h * 128;
    const uint32_t pdst = mapa(sb + OFF_U + (q & 1) * 2 * U_PITCH + 32 + rank * 512 + g * 16 + h * 128, q >> 1), pbar = mapa(BAR(B_U), q >> 1);
    asm volatile("barrier.cluster.wait.aligned;" ::: "memory");
#pragma unroll 1
    for (int pc = 0; pc < 4; pc++) {
      mbar_wait(BAR(B_KV + pc), 0);
      SSTAMP(h == 0 && lane == 0, 42 + pc);
      prep_task(psrc + pc * KV_PIECE, pdst + pc * 1024, pbar + pc * 8, w0, w1, w2, w3);
      SSTAMP(h == 0 && lane == 0 && pc == 0, 27);
    }
    __syncwarp();
    if (lane == 0) mbar_arrive(BAR(B_PREPD));
    SSTAMP(h == 0 && lane == 0, 51);
    if (bid < 86) {
      const int which = bid >= 43, unit = bid - which * 43;
      uint32_t wa = sb + OFF_KV + h * 8192 + g * 64 + ((q ^ (g >> 1)) * 16);
      uint16_t* d = p.scr->wX + (size_t)((unit - 40) * 2 + (q >> 1)) * (D_ * 32) + (h * 128 + g) * 32 + ((which * 2 + (q & 1)) ^ (g >> 1)) * 8;
      float cs[8];
#pragma unroll
      for (int i = 0; i < 8; i++) cs[i] = 0.f;
      mbar_wait(BAR(B_CW), 0);
      mbar_wait(BAR(B_SIGE + 1), 0);
#pragma unroll 1
      for (int b = 0; b < 4; b++) {
        uint4 v[4];
#pragma unroll
        for (int i = 0; i < 4; i++) v[i] = lds128(wa + i * 512);
#pragma unroll
        for (int i = 0; i < 4; i++) {
          cs[0] += blo(v[i].x); cs[1] += bhi(v[i].x); cs[2] += blo(v[i].y); cs[3] += bhi(v[i].y);
          cs[4] += blo(v[i].z); cs[5] += bhi(v[i].z); cs[6] += blo(v[i].w); cs[7] += bhi(v[i].w);
        }
        if (unit >= 40) {
#pragma unroll
          for (int i = 0; i < 4; i++) *(uint4*)(d + i * 256) = v[i];
        }
        d += 1024; wa += 2048;
      }
#pragma unroll 1
      for (int o = 4; o < 32; o <<= 1)
#pragma unroll
        for (int i = 0; i < 8; i++) cs[i] += __shfl_xor_sync(0xffffffffu, cs[i], o);
      if (lane < 4) {
        sts128f(sb + OFF_CS + h * 128 + lane * 32, cs[0], cs[1], cs[2], cs[3]);
        sts128f(sb + OFF_CS + h * 128 + lane * 32 + 16, cs[4], cs[5], cs[6], cs[7]);
      }
      STAMP_IF(h == 0 && lane == 0, 53);
    }
    __syncwarp();
    if (lane == 0) mbar_arrive(BAR(B_CSD));
    const int ck = rank * 4 + h;
    const uint32_t sdst = mapa(sb + OFF_STX + (ck * 8 + g) * 8, q & 1), sbar = mapa(BAR(B_STX), q & 1);
#pragma unroll 1
    for (int w = 0; w < 2; w++) {
      uint32_t la = sb + OFF_A + w * 65536 + lane * 128 + ((ck ^ (lane & 7)) * 16);
      float s0 = 0.f, s1 = 0.f, q0 = 0.f, q1 = 0.f, c = 0.f;
#pragma unroll 1
      for (int s = 0; s < 8; s++) {
        uint32_t m[8];
        mbar_wait(BAR(B_FULLA + w * 8 + s), 0);
        ldsm4t(la, m[0], m[1], m[2], m[3]); ldsm4t(la + 4096, m[4], m[5], m[6], m[7]);
        la += 8192;
        if (STAT_SHIFT && s == 0) c = __shfl_sync(0xffffffffu, blo(m[0]), lane & ~3);
#pragma unroll
        for (int i = 0; i < 8; i++) {
          float d0 = blo(m[i]), d1 = bhi(m[i]);
          if (STAT_SHIFT) { d0 -= c; d1 -= c; }
          s0 += d0; s1 += d1; q0 = fmaf(d0, d0, q0); q1 = fmaf(d1, d1, q1);
        }
      }
      s0 += s1; q0 += q1;
#pragma unroll
      for (int o = 1; o < 4; o <<= 1) { s0 += __shfl_xor_sync(0xffffffffu, s0, o); q0 += __shfl_xor_sync(0xffffffffu, q0, o); }
      const float md = s0 * (1.f / D_), var = fmaxf(fmaf(-md, md, q0 * (1.f / D_)), 0.f);
      if (q < 2) asm volatile("st.async.weak.shared::cluster.mbarrier::complete_tx::bytes.v2.f32 [%0], {%1,%2}, [%3];"
                              :: "r"(sdst + w * 512), "f"(-(md + c)), "f"(rsqrtf(var + 1e-5f)), "r"(sbar + w * 8) : "memory");
      STAMP_IF(h == 0 && lane == 0, 46 + w);
    }
  } else {
    asm volatile("setmaxnreg.dec.sync.aligned.u32 40;");
    const int h = warp - 12;
    asm volatile("barrier.cluster.wait.aligned;" ::: "memory");
    if (h == 0) {
      if (elect()) {
#pragma unroll
        for (int pc = 1; pc < 4; pc++) {
          if (pc == KV_HOLD) mbar_wait(BAR(B_GO), 0);
          kv_load(pc);
        }
        const int cw = js * 64, c3 = 1024 + js * 32, co = cw ^ 64, kr = rank * 256, b3 = js < 6 ? 12288 : 8192;
        const uint16_t* wx = p.scr->wX + (size_t)js * (D_ * 32);
        mbar_wait(BAR(B_GO), 0);
        mbar_wait(BAR(B_KV + 3), 0);
#pragma unroll
        for (int r = 0; r < 35; r++) {
          const int slot = r % 6;
          const uint32_t b = BAR(B_FULLR + slot), d = sb + OFF_RING + slot * 16384;
          if (r == 3) {
            if (bid < 86) {
              mbar_wait(BAR(B_PREPD), 0);
              fence_async_s();
              mbar_expect(BAR(B_CW), 32768);
#pragma unroll 1
              for (int i = 0; i < 8; i++) tma2d(sb + OFF_KV + i * 4096, bid >= 43 ? &tmU32 : &tmG32, (bid >= 43 ? bid - 43 : bid) * 32, i * 64, BAR(B_CW));
            }
            STAMP(28);
            mbar_wait(BAR(B_GO + 1), 0);
            fence_async_s();
          }
          if (r == 10) asm volatile("cp.async.bulk.prefetch.L2.global [%0], %1;" :: "l"((const char*)p.wd + (size_t)bid * 11008), "r"(11008) : "memory");
          if (r == 16) mbar_wait(BAR(B_CS), 0);
          if (r >= 6) mbar_wait(BAR(B_EMPTYR + slot), (r / 6 - 1) & 1);
          const int dep = r < 24 ? R_DEPTH : R2_DEPTH;
          if (dep < 6 && r >= dep) mbar_wait(BAR(B_FULLR + (r - dep) % 6), ((r - dep) / 6) & 1);
          if (r < 16) {
            mbar_expect(b, 16384);
            tma2d(d, &tmG, cw + (r >> 3) * 512, (r & 7) * 64, b); tma2d(d + 8192, &tmU, cw + (r >> 3) * 512, (r & 7) * 64, b);
          } else if (r < 24) {
            mbar_expect(b, b3);
            tma2d(d, &tmG32, c3, (r & 7) * 64, b); tma2d(d + 4096, &tmU32, c3, (r & 7) * 64, b);
            if (js < 6) bulk_ld(d + 8192, wx + (r & 7) * 2048, 4096, b);
          } else if (r < 32) {
            const int k = kr + ((r & 4) * 2 + (r & 3)) * 64;
            mbar_expect(b, 16384);
            tma2d(d, &tmD, cw, k, b); tma2d(d + 8192, &tmD, co, k, b);
          } else {
            mbar_expect(b, 16384);
            tma2d(d, &tmD, cw, 1024 + (r - 32) * 128, b); tma2d(d + 8192, &tmD, cw, 1088 + (r - 32) * 128, b);
          }
        }
        p.scr->epoch[bid] = small.x + 1;
      }
    } else if (h == 3) {
#pragma unroll 1
      for (int i = 0; i < 7; i++) {
        mbar_wait_bounded(BAR(B_SIG + i), 0);
        if (i == 6) break;
        unsigned* c = &p.scr->cnt[(i == 0 ? CNT_X : i < 3 ? CNT_E + (i - 1) * 8 + (bid >> 4) : CNT_H + tile * 3 + i - 3) * 32];
        if (i == 0) {
          fence_async_s();
          if (elect()) {
            asm volatile("cp.async.bulk.tensor.2d.global.shared::cta.bulk_group [%0, {%2, %3}], [%1];" :: "l"(&tmX), "r"(sb + OFF_XST), "r"(bid * 64), "r"(0) : "memory");
            asm volatile("cp.async.bulk.global.shared::cta.bulk_group [%0], [%1], 64;" :: "l"(p.scr->st1 + bid * 16), "r"(sb + OFF_CS) : "memory");
            asm volatile("cp.async.bulk.commit_group;" ::: "memory");
            asm volatile("cp.async.bulk.wait_group 0;" ::: "memory");
          }
          __syncwarp();
        }
        if (lane == 0) { signal_gpu(c); if (i == 0 || i == 2) mbar_arrive(BAR(B_GO + (i >> 1))); }
        __syncwarp();
        STAMP_IF(lane == 0, i == 0 ? 50 : 53 + i);
        if (i == 2 && bid < 86) {
          const int which = bid >= 43, f = (bid - which * 43) * 32 + lane;
          mbar_wait_bounded(BAR(B_CSD), 0);
          const uint32_t a = sb + OFF_CS + lane * 4;
          p.scr->cs[(f >> 1) * 4 + which * 2 + (f & 1)] = __uint_as_float(lds32(a)) + __uint_as_float(lds32(a + 128)) + __uint_as_float(lds32(a + 256)) + __uint_as_float(lds32(a + 384));
          __syncwarp();
          if (lane == 0) signal_gpu(&p.scr->cnt[CNT_C * 32]);
          __syncwarp();
          STAMP_IF(lane == 0, 29);
        }
      }
    } else {
      const unsigned ep = small.x + 1;
      const int w = h - 1, blk = tile + 16 * w;
      const uint32_t aw = sb + OFF_A + w * 65536;
      const uint32_t fullA = BAR(B_FULLA + w * 8), emptyA = BAR(B_EMPTYA + w * 6);
      if (w == 0) {
        if (elect()) {
          mbar_wait(BAR(B_GO), 0);
          poll1(&p.scr->cnt[CNT_X * 32], ep * NCTA);
          fence_async_g(); fence_async_s();
          uint32_t b = BAR(B_XT);
          mbar_expect(b, 12288); mbar_expect(b + 8, 12288);
          bulk_ld(sb + OFF_XTE, p.scr->xT + (size_t)bid * 8192, 8192, b);
          bulk_ld(sb + OFF_STE, p.scr->st1, 4096, b);
          bulk_ld(sb + OFF_XTL, p.scr->xT + (size_t)bid * 8192 + 4096, 8192, b + 8);
          bulk_ld(sb + OFF_STL, p.scr->st1 + 1024, 4096, b + 8);
          SSTAMP(true, 52);
        }
        __syncwarp();
      }
      const uint16_t* asrc = p.scr->hT + (size_t)blk * (D_ * 64);
      const uint16_t* hsrc = p.scr->H + (size_t)blk * (86 * 1024);
      const uint16_t* hsp = hsrc + rank * 16384;
      const unsigned* hc = &p.scr->cnt[(CNT_H + tile * 3) * 32];
      mbar_wait(BAR(B_SIGE + w), 0);
      fence_async_s();
      poll_ge(&p.scr->cnt[(CNT_E + w * 8 + (lane & 7)) * 32], ep * 16, lane < 8);
      STAMP_IF(lane == 0, 59 + w);
      if (elect()) {
        if (A_AFTER_GO) mbar_wait(BAR(B_GO + 1), 0);
        if (w == 0) { mbar_wait(BAR(B_CSD), 0); fence_async_s(); }
        fence_async_g();
#pragma unroll
        for (int s = 0; s < 8; s++) {
          if (s >= A_DEPTH) mbar_wait(fullA + (s - A_DEPTH) * 8, 0);
          mbar_expect(fullA + s * 8, 8192);
          bulk_ld(aw + s * 8192, asrc + s * 4096, 8192, fullA + s * 8);
        }
        if (w == 0) {
          poll1(&p.scr->cnt[CNT_C * 32], ep * 86);
          fence_async_g(); fence_async_s();
          uint32_t b = BAR(B_CS), d = sb + OFF_CS;
          mbar_expect(b, js < 6 ? 1408 : 1280);
          bulk_ld(d, p.scr->cs + js * 128, 512, b);
          bulk_ld(d + 512, p.scr->cs + 1024 + js * 128, 512, b);
          bulk_ld(d + 1024, p.scr->cs + 2048 + js * 64, 256, b);
          if (js < 6) bulk_ld(d + 1280, p.scr->cs + 2560 + js * 32, 128, b);
          STAMP(30);
        }
#pragma unroll
        for (int s = 0; s < 14; s++) {
          const int slot = s % 6;
          if ((s & 3) == 0 && s < 12) {
            mbar_wait(BAR(B_SIGH + (s >> 2)), 0);
            poll1(hc + (s >> 2) * 32, ep * 8);
            fence_async_g();
            STAMP_IF(w == 0, 61 + (s >> 2));
          }
          mbar_wait(emptyA + slot * 8, (s / 6) & 1);
          const int dep = s < 8 ? H_DEPTH : H3_DEPTH;
          if (dep < 6 && s >= dep) mbar_wait(fullA + ((s - dep) % 6) * 8, ((s - dep) / 6 + 1) & 1);
          mbar_expect(fullA + slot * 8, s == 13 ? 4096 : 8192);
          bulk_ld(aw + slot * 8192, s < 8 ? hsp + ((s & 4) * 2 + (s & 3)) * 4096 : hsrc + (s + 8) * 4096, s == 13 ? 4096 : 8192, fullA + slot * 8);
        }
      }
    }
  }
}

typedef CUresult (*EncFn)(CUtensorMap*, CUtensorMapDataType, cuuint32_t, void*, const cuuint64_t*, const cuuint64_t*,
                          const cuuint32_t*, const cuuint32_t*, CUtensorMapInterleave, CUtensorMapSwizzle,
                          CUtensorMapL2promotion, CUtensorMapFloatOOBfill);

void make_map(EncFn fn, CUtensorMap* tm, const void* ptr, int w, int hgt, int bw, int bh, CUtensorMapSwizzle sw, CUtensorMapL2promotion pr) {
  cuuint64_t dims[2] = {(cuuint64_t)w, (cuuint64_t)hgt};
  cuuint64_t str[1] = {(cuuint64_t)w * 2};
  cuuint32_t box[2] = {(cuuint32_t)bw, (cuuint32_t)bh}, es[2] = {1, 1};
  fn(tm, CU_TENSOR_MAP_DATA_TYPE_BFLOAT16, 2, (void*)ptr, dims, str, box, es, CU_TENSOR_MAP_INTERLEAVE_NONE, sw, pr,
     CU_TENSOR_MAP_FLOAT_OOB_FILL_NONE);
}

void make_map_runs(EncFn fn, CUtensorMap* tm, const void* ptr) {
  cuuint64_t dims[3] = {(cuuint64_t)D_, (cuuint64_t)(S_ / 8), 8};
  cuuint64_t str[2] = {(cuuint64_t)D_ * 16, (cuuint64_t)D_ * 2};
  cuuint32_t box[3] = {8, 33, 8}, es[3] = {1, 1, 1};
  fn(tm, CU_TENSOR_MAP_DATA_TYPE_BFLOAT16, 3, (void*)ptr, dims, str, box, es, CU_TENSOR_MAP_INTERLEAVE_NONE,
     CU_TENSOR_MAP_SWIZZLE_NONE, CU_TENSOR_MAP_L2_PROMOTION_L2_128B, CU_TENSOR_MAP_FLOAT_OOB_FILL_NONE);
}

}

extern "C" void kernel_launch(void* const* d_in, const int* in_sizes, int n_in, void* d_out, int out_size) {
  (void)in_sizes; (void)n_in; (void)out_size;
  static EncFn fn = nullptr;
  if (!fn) {
    void* f = nullptr; cudaDriverEntryPointQueryResult qr;
    cudaGetDriverEntryPoint("cuTensorMapEncodeTiled", &f, cudaEnableDefault, &qr);
    fn = (EncFn)f;
    cudaFuncSetAttribute(fused_kernel, cudaFuncAttributeMaxDynamicSharedMemorySize, SMEM_BYTES);
  }
  CUtensorMap tmK, tmV, tmG, tmU, tmG32, tmU32, tmD, tmX, tmT;
  void* xT = nullptr;
  cudaGetSymbolAddress(&xT, g_scr);
  make_map(fn, &tmX, xT, 8192, 128, 64, 128, CU_TENSOR_MAP_SWIZZLE_NONE, CU_TENSOR_MAP_L2_PROMOTION_NONE);
  {
    cuuint64_t dims[3] = {16, (cuuint64_t)(S_ / 16), (cuuint64_t)D_};
    cuuint64_t str[2] = {32, (cuuint64_t)S_ * 2};
    cuuint32_t box[3] = {16, 136, 2}, es[3] = {1, 1, 1};
    fn(&tmT, CU_TENSOR_MAP_DATA_TYPE_BFLOAT16, 3, d_in[4], dims, str, box, es, CU_TENSOR_MAP_INTERLEAVE_NONE,
       CU_TENSOR_MAP_SWIZZLE_32B, CU_TENSOR_MAP_L2_PROMOTION_L2_128B, CU_TENSOR_MAP_FLOAT_OOB_FILL_NONE);
  }
  make_map_runs(fn, &tmK, d_in[1]);
  make_map_runs(fn, &tmV, d_in[2]);
  make_map(fn, &tmG, d_in[7], F_, D_, 64, 64, CU_TENSOR_MAP_SWIZZLE_128B, CU_TENSOR_MAP_L2_PROMOTION_NONE);
  make_map(fn, &tmU, d_in[8], F_, D_, 64, 64, CU_TENSOR_MAP_SWIZZLE_128B, CU_TENSOR_MAP_L2_PROMOTION_NONE);
  make_map(fn, &tmG32, d_in[7], F_, D_, 32, 64, CU_TENSOR_MAP_SWIZZLE_64B, CU_TENSOR_MAP_L2_PROMOTION_NONE);
  make_map(fn, &tmU32, d_in[8], F_, D_, 32, 64, CU_TENSOR_MAP_SWIZZLE_64B, CU_TENSOR_MAP_L2_PROMOTION_NONE);
  make_map(fn, &tmD, d_in[9], D_, F_, 64, 64, CU_TENSOR_MAP_SWIZZLE_128B, CU_TENSOR_MAP_L2_PROMOTION_NONE);
  Params p;
  p.x = (const uint16_t*)d_in[0]; p.shift_k = (const uint16_t*)d_in[3]; p.ssm_k = (const uint16_t*)d_in[4];
  p.ssm_D = (const uint16_t*)d_in[5]; p.wg = (const uint16_t*)d_in[7]; p.wu = (const uint16_t*)d_in[8];
  p.wd = (const uint16_t*)d_in[9]; p.out = (uint16_t*)d_out; p.scr = (Scratch*)xT; p.i128 = 128; p.i64 = 64; p.im1 = -2; p.z64 = 0;
  cudaLaunchConfig_t cfg = {};
  cfg.gridDim = dim3(NCTA); cfg.blockDim = dim3(NTHR); cfg.dynamicSmemBytes = SMEM_BYTES; cfg.stream = cudaStreamPerThread;
  cudaLaunchAttribute at[1];
  at[0].id = cudaLaunchAttributeClusterDimension; at[0].val.clusterDim.x = 2; at[0].val.clusterDim.y = 1; at[0].val.clusterDim.z = 1;
  cfg.attrs = at; cfg.numAttrs = 1;
  cudaLaunchKernelEx(&cfg, fused_kernel, p, tmK, tmV, tmG, tmU, tmG32, tmU32, tmD, tmX, tmT);
}
```

```cpp
#include <cuda_runtime.h>
#include <cuda_bf16.h>
#include <cuda.h>
#include <stdint.h>

namespace {

constexpr int S_ = 2048, D_ = 512, F_ = 1376;
constexpr int NCTA = 128, NTHR = 512;
#define FFN_MAP 0
#define STAT_SHIFT 0
#define EPI1_FAST 1
#define CONV_ORDER 0
#define CONV_TAIL 0
#define PREP_FMA 1
#define KV1_T 0
#define KV2_T 0
#define KV3_T 0
#define KV_EVT 2
#define A_AFTER_GO 1
#define A_DEPTH0 3
#define R_AFTER_A 1
#define WIN 56
#define WIN3 200
#define BASE_AT 13
#define ORD 0
#define W3_FROM 50
#define W2_FROM 36
#define WINA WIN
#define SEND_AT 8
#define SEND_N 2
#define GPC_MAP 1
#define KV_HOLD 0

#define A_DEPTH 3
#define WIN1 36

struct __align__(1024) Scratch {
  uint16_t xT[D_ * S_];
  uint16_t hT[32 * D_ * 64];
  uint16_t H[32 * 86 * 1024];
  uint16_t wX[6 * D_ * 32];
  uint32_t st1[S_];
  float    cs[F_ * 2];
  unsigned cnt[(4 + 48) * 32];
  unsigned epoch[NCTA];
};
__device__ Scratch g_scr;
#define STAMP(id)
#define STAMP_IF(c, id)
#define TW(acc, stmt) stmt
#define TWOUT(c, id, acc)
#define SSTAMP(c, id)
#define STAMP_NS(c, id)
constexpr int CNT_X = 0, CNT_E = 1, CNT_C = 3, CNT_H = 4;
__host__ __device__ constexpr int tok(int b, int tau) { return 128 * (b >> 1) + 16 * (tau & 7) + 8 * (b & 1) + ((tau >> 3) ^ 1); }

constexpr uint32_t OFF_A    = 0;
constexpr uint32_t OFF_RING = 131072;
constexpr uint32_t OFF_CS   = 229376;
constexpr uint32_t OFF_BAR  = OFF_CS + 1408;
constexpr uint32_t OFF_STX  = OFF_BAR + 640;
constexpr uint32_t SMEM_BYTES = 232448;
constexpr uint32_t KV_PIECE = 8448;
constexpr uint32_t OFF_KV   = 65536 - 4 * KV_PIECE;
constexpr uint32_t OFF_CW   = 32768;
constexpr uint32_t OFF_XR   = 0;
constexpr uint32_t OFF_XTE  = OFF_XR;
constexpr uint32_t OFF_STE  = OFF_XR + 8192;
constexpr uint32_t U_PITCH  = 8352, U_ODD = 4160;
constexpr uint32_t T_PITCH  = 4352;
constexpr uint32_t OFF_TAP  = 65536;
constexpr uint32_t OFF_U    = OFF_TAP + 4 * T_PITCH;
constexpr uint32_t OFF_XTL  = OFF_U + 4 * U_PITCH;
constexpr uint32_t OFF_STL  = OFF_XTL + 8192;
constexpr uint32_t OFF_XST  = OFF_RING + 2 * 16384;
constexpr uint32_t OFF_XCH  = OFF_RING + 3 * 16384;
static_assert(OFF_XR % 1024 == 0 && OFF_XR + 16384 <= 65536, "");
static_assert(OFF_STL + 4096 <= 131072, "");
static_assert(OFF_STX + 1024 <= SMEM_BYTES, "");
constexpr int B_EMPTYR = 0  , B_SIG = 6  ,
              B_EMPTYA = 20  , B_PEER = 32  , B_PREPD = 34, B_CSD = 35,
              B_KV = 40  , B_XR = 44, B_TAP = 45  , B_CS = 47, B_GO = 48  ,
              B_U = 50  , B_RECV = 54  , B_STX = 56  , B_XT = 58  , B_FULLA = 60  , B_CW = 76, B_SEEN = 77  ,
              B_FULLR = 14  ;
constexpr int B_SIGX = B_SIG, B_SIGE = B_SIG + 1, B_SIGH = B_SIG + 3;

#define HH(s) 64 + 2 * (s), 65 + 2 * (s)
constexpr int SCHED_N = 22 + 13 + 28;
constexpr int SCHED[SCHED_N] = {0, 1, 2, 3, 4, 5, 6, 7, 8, 9, 10, 11, 12, 13, 14, 15, 16, 17, 18, 19, 20, 21,
  22, HH(0), 23, HH(1), 24, HH(2), 25, HH(3), 26, 27, 28, HH(4), 29, HH(5), 30, HH(6), 31, HH(7), 32, 33,
  HH(8), HH(9), 34, HH(10), HH(11), HH(12), HH(13)};
constexpr int sched_kb(int v) { return v >= 64 ? 8 : v >= 16 && v < 24 ? 12 : 16; }
constexpr int sched_dep(int i) {
  int best = -1;
  for (int k = 0; k <= i; k++) {
    int acc = 0, win = k < 22 ? WIN1 : (k >= W3_FROM ? WIN3 : k >= W2_FROM ? WIN : WINA);
    for (int j = k; j >= 0; j--) { acc += sched_kb(SCHED[j]); if (acc > win) { if (j > best) best = j; break; } }
  }
  return best;
}
constexpr bool sched_reused(int j, int i) {
  for (int k = j + 1; k <= i; k++) if (SCHED[k] == SCHED[j] + (SCHED[j] < 64 ? 6 : 12)) return true;
  return false;
}
template <int I> struct SchedDep { static constexpr int v = sched_dep(I); };
template <int J, int I> struct SchedReused { static constexpr bool v = sched_reused(J, I); };
template <int I> struct IC { static constexpr int v = I; };
template <int I, int E, class F> __device__ __forceinline__ void static_for(F&& f) { if constexpr (I < E) { f(IC<I>{}); static_for<I + 1, E>(f); } }

__device__ __forceinline__ uint32_t s2u(const void* p) { return (uint32_t)__cvta_generic_to_shared(p); }
__device__ __forceinline__ void mbar_init(uint32_t b, int n) { asm volatile("mbarrier.init.shared::cta.b64 [%0], %1;" :: "r"(b), "r"(n) : "memory"); }
__device__ __forceinline__ void mbar_expect(uint32_t b, int bytes) { asm volatile("mbarrier.arrive.expect_tx.shared::cta.b64 _, [%0], %1;" :: "r"(b), "r"(bytes) : "memory"); }
__device__ __forceinline__ void mbar_arrive(uint32_t b) { asm volatile("mbarrier.arrive.shared::cta.b64 _, [%0];" :: "r"(b) : "memory"); }
#define MBAR_WAIT_ASM(SEM) \
  asm volatile("{\n .reg .pred p;\nSPIN:\n mbarrier.try_wait.parity" SEM ".shared::cta.b64 p, [%0], %1;\n @!p bra SPIN;\n}" :: "r"(b), "r"(par) : "memory")
__device__ __forceinline__ void mbar_wait(uint32_t b, int par) { MBAR_WAIT_ASM(""); }
__device__ __forceinline__ void mbar_wait_cluster(uint32_t b, int par) {
  MBAR_WAIT_ASM("");
  asm volatile("fence.acquire.sync_restrict::shared::cluster.cluster;" ::: "memory");
}
__device__ __forceinline__ void mbar_wait_bounded(uint32_t b, int par) {
  asm volatile("{\n .reg .pred p, t; .reg .u32 c;\n mov.u32 c, 0;\n"
    "SPIN:\n mbarrier.try_wait.parity.shared::cta.b64 p, [%0], %1;\n @p bra DONE;\n"
    " add.u32 c, c, 1;\n setp.lt.u32 t, c, 1048576;\n @t bra SPIN;\n trap;\nDONE:\n}" :: "r"(b), "r"(par) : "memory");
}
__device__ __forceinline__ uint32_t mapa(uint32_t a, int r) { uint32_t d; asm("mapa.shared::cluster.u32 %0, %1, %2;" : "=r"(d) : "r"(a), "r"(r)); return d; }
__device__ __forceinline__ void st_async4(uint32_t a, uint32_t x, uint32_t y, uint32_t z, uint32_t w, uint32_t bar) {
  asm volatile("st.async.weak.shared::cluster.mbarrier::complete_tx::bytes.v4.b32 [%0], {%1,%2,%3,%4}, [%5];" :: "r"(a), "r"(x), "r"(y), "r"(z), "r"(w), "r"(bar) : "memory");
}
__device__ __forceinline__ void tma3d(uint32_t dst, const CUtensorMap* tm, int c0, int c1, int c2, uint32_t bar) {
  asm volatile("cp.async.bulk.tensor.3d.shared::cluster.global.mbarrier::complete_tx::bytes [%0], [%1, {%3, %4, %5}], [%2];" :: "r"(dst), "l"(tm), "r"(bar), "r"(c0), "r"(c1), "r"(c2) : "memory");
}
__device__ __forceinline__ void sts64(uint32_t a, uint32_t x, uint32_t y) { asm volatile("st.shared.v2.b32 [%0], {%1,%2};" :: "r"(a), "r"(x), "r"(y) : "memory"); }
__device__ __forceinline__ bool elect() { uint32_t p; asm volatile("{ .reg .pred P; elect.sync _|P, 0xffffffff; selp.u32 %0, 1, 0, P; }" : "=r"(p)); return p; }
__device__ __forceinline__ void bulk_ld(uint32_t dst, const void* src, int bytes, uint32_t bar) {
  asm volatile("cp.async.bulk.shared::cluster.global.mbarrier::complete_tx::bytes [%0], [%1], %2, [%3];" :: "r"(dst), "l"(src), "r"(bytes), "r"(bar) : "memory");
}
__device__ __forceinline__ void tma2d(uint32_t dst, const CUtensorMap* tm, int c0, int c1, uint32_t bar) {
  asm volatile("cp.async.bulk.tensor.2d.shared::cluster.global.mbarrier::complete_tx::bytes [%0], [%1, {%3, %4}], [%2];" :: "r"(dst), "l"(tm), "r"(bar), "r"(c0), "r"(c1) : "memory");
}
__device__ __forceinline__ void fence_async_g() { asm volatile("fence.proxy.async.global;" ::: "memory"); }
__device__ __forceinline__ void fence_async_s() { asm volatile("fence.proxy.async.shared::cta;" ::: "memory"); }
__device__ __forceinline__ void poll1(const unsigned* p, unsigned target) {
  unsigned v;
  do { asm volatile("ld.relaxed.gpu.global.u32 %0, [%1];" : "=r"(v) : "l"(p) : "memory"); } while ((int)(v - target) < 0);
  asm volatile("fence.acquire.gpu;" ::: "memory");
}
__device__ __forceinline__ void signal_gpu(unsigned* p) {
  fence_async_g();
  asm volatile("red.release.gpu.global.add.u32 [%0], 1;" :: "l"(p) : "memory");
}
__device__ __forceinline__ void bar_sync(int id, int n) { asm volatile("bar.sync %0, %1;" :: "r"(id), "r"(n) : "memory"); }
__device__ __forceinline__ void bar_arrive(int id, int n) { asm volatile("bar.arrive %0, %1;" :: "r"(id), "r"(n) : "memory"); }
__device__ __forceinline__ uint32_t lds32(uint32_t a) { uint32_t v; asm volatile("ld.shared.b32 %0, [%1];" : "=r"(v) : "r"(a)); return v; }
__device__ __forceinline__ uint2 lds64(uint32_t a) { uint2 v; asm volatile("ld.shared.v2.b32 {%0,%1}, [%2];" : "=r"(v.x), "=r"(v.y) : "r"(a)); return v; }
__device__ __forceinline__ uint4 lds128(uint32_t a) { uint4 v; asm volatile("ld.shared.v4.b32 {%0,%1,%2,%3}, [%4];" : "=r"(v.x), "=r"(v.y), "=r"(v.z), "=r"(v.w) : "r"(a)); return v; }
__device__ __forceinline__ float4 lds128f(uint32_t a) { float4 v; asm volatile("ld.shared.v4.f32 {%0,%1,%2,%3}, [%4];" : "=f"(v.x), "=f"(v.y), "=f"(v.z), "=f"(v.w) : "r"(a)); return v; }
__device__ __forceinline__ void sts32(uint32_t a, uint32_t v) { asm volatile("st.shared.b32 [%0], %1;" :: "r"(a), "r"(v) : "memory"); }
__device__ __forceinline__ void sts128f(uint32_t a, float x, float y, float z, float w) { asm volatile("st.shared.v4.f32 [%0], {%1,%2,%3,%4};" :: "r"(a), "f"(x), "f"(y), "f"(z), "f"(w) : "memory"); }
__device__ __forceinline__ void ldsm4t(uint32_t a, uint32_t& r0, uint32_t& r1, uint32_t& r2, uint32_t& r3) {
  asm volatile("ldmatrix.sync.aligned.m8n8.x4.trans.shared.b16 {%0,%1,%2,%3}, [%4];" : "=r"(r0), "=r"(r1), "=r"(r2), "=r"(r3) : "r"(a));
}
__device__ __forceinline__ void stsm4(uint32_t a, uint32_t r0, uint32_t r1, uint32_t r2, uint32_t r3) {
  asm volatile("stmatrix.sync.aligned.m8n8.x4.shared.b16 [%0], {%1,%2,%3,%4};" :: "r"(a), "r"(r0), "r"(r1), "r"(r2), "r"(r3) : "memory");
}
__device__ __forceinline__ uint32_t bmul(uint32_t a, uint32_t b) { uint32_t d; asm("mul.rn.bf16x2 %0, %1, %2;" : "=r"(d) : "r"(a), "r"(b)); return d; }
__device__ __forceinline__ uint32_t badd(uint32_t a, uint32_t b) { uint32_t d; asm("add.rn.bf16x2 %0, %1, %2;" : "=r"(d) : "r"(a), "r"(b)); return d; }
__device__ __forceinline__ uint32_t bfma(uint32_t a, uint32_t b, uint32_t c) { uint32_t d; asm("fma.rn.bf16x2 %0, %1, %2, %3;" : "=r"(d) : "r"(a), "r"(b), "r"(c)); return d; }
__device__ __forceinline__ float blo(uint32_t v) { return __uint_as_float(v << 16); }
__device__ __forceinline__ float bhi(uint32_t v) { return __uint_as_float(v & 0xffff0000u); }
__device__ __forceinline__ uint32_t pack2(float lo, float hi) { uint32_t d; asm("cvt.rn.bf16x2.f32 %0, %1, %2;" : "=r"(d) : "f"(hi), "f"(lo)); return d; }
__device__ __forceinline__ uint64_t mkdesc(uint32_t addr, uint32_t lbo, uint32_t sbo, int swz) {
  return (uint64_t)((addr & 0x3FFFF) >> 4) | ((uint64_t)(lbo >> 4) << 16) | ((uint64_t)(sbo >> 4) << 32) | ((uint64_t)swz << 62);
}
__device__ __forceinline__ void wg_fence() { asm volatile("wgmma.fence.sync.aligned;" ::: "memory"); }
__device__ __forceinline__ void wg_commit() { asm volatile("wgmma.commit_group.sync.aligned;" ::: "memory"); }
template <int N> __device__ __forceinline__ void wg_wait() { asm volatile("wgmma.wait_group.sync.aligned %0;" :: "n"(N) : "memory"); }
template <int I0, int I1, int N> __device__ __forceinline__ void reg_fence(float (&d)[N]) {
#pragma unroll
  for (int i = I0; i < I1; i++) asm volatile("" : "+f"(d[i]) :: "memory");
}
template <int I0, int I1, int N> __device__ __forceinline__ void reg_rename(float (&d)[N]) {
#pragma unroll
  for (int i = I0; i < I1; i++) { float t; asm volatile("mov.b32 %0, %1;" : "=f"(t) : "f"(d[i]) : "memory"); d[i] = t; }
}
template <int TA, int TB, int SZ>
__device__ __forceinline__ void wgmma_n64(float (&d)[SZ], uint64_t& a, int ai, uint64_t& b, int bi, int sd) {
  asm volatile("{ .reg .pred p; .reg .b32 l0, h0, l1, h1; setp.ne.b32 p, %36, 0;\n"
    "wgmma.mma_async.sync.aligned.m64n64k16.f32.bf16.bf16 {%0, %1, %2, %3, %4, %5, %6, %7, %8, %9, %10, %11, %12, %13, %14, %15, %16, %17, %18, %19, %20, %21, %22, %23, %24, %25, %26, %27, %28, %29, %30, %31}, %32, %33, p, 1, 1, %37, %38;\n"
    "mov.b64 {l0, h0}, %32; add.s32 l0, l0, %34; mov.b64 %32, {l0, h0};\n"
    "mov.b64 {l1, h1}, %33; add.s32 l1, l1, %35; mov.b64 %33, {l1, h1}; }"
    : "+f"(d[0]), "+f"(d[1]), "+f"(d[2]), "+f"(d[3]), "+f"(d[4]), "+f"(d[5]), "+f"(d[6]), "+f"(d[7]), "+f"(d[8]), "+f"(d[9]), "+f"(d[10]), "+f"(d[11]), "+f"(d[12]), "+f"(d[13]), "+f"(d[14]), "+f"(d[15]), "+f"(d[16]), "+f"(d[17]), "+f"(d[18]), "+f"(d[19]), "+f"(d[20]), "+f"(d[21]), "+f"(d[22]), "+f"(d[23]), "+f"(d[24]), "+f"(d[25]), "+f"(d[26]), "+f"(d[27]), "+f"(d[28]), "+f"(d[29]), "+f"(d[30]), "+f"(d[31]), "+l"(a), "+l"(b)
    : "r"(ai), "r"(bi), "r"(sd), "n"(TA), "n"(TB));
}
template <int TA, int TB, int SZ>
__device__ __forceinline__ void wgmma_n96(float (&d)[SZ], uint64_t& a, int ai, uint64_t& b, int bi, int sd) {
  asm volatile("{ .reg .pred p; .reg .b32 l0, h0, l1, h1; setp.ne.b32 p, %52, 0;\n"
    "wgmma.mma_async.sync.aligned.m64n96k16.f32.bf16.bf16 {%0, %1, %2, %3, %4, %5, %6, %7, %8, %9, %10, %11, %12, %13, %14, %15, %16, %17, %18, %19, %20, %21, %22, %23, %24, %25, %26, %27, %28, %29, %30, %31, %32, %33, %34, %35, %36, %37, %38, %39, %40, %41, %42, %43, %44, %45, %46, %47}, %48, %49, p, 1, 1, %53, %54;\n"
    "mov.b64 {l0, h0}, %48; add.s32 l0, l0, %50; mov.b64 %48, {l0, h0};\n"
    "mov.b64 {l1, h1}, %49; add.s32 l1, l1, %51; mov.b64 %49, {l1, h1}; }"
    : "+f"(d[0]), "+f"(d[1]), "+f"(d[2]), "+f"(d[3]), "+f"(d[4]), "+f"(d[5]), "+f"(d[6]), "+f"(d[7]), "+f"(d[8]), "+f"(d[9]), "+f"(d[10]), "+f"(d[11]), "+f"(d[12]), "+f"(d[13]), "+f"(d[14]), "+f"(d[15]), "+f"(d[16]), "+f"(d[17]), "+f"(d[18]), "+f"(d[19]), "+f"(d[20]), "+f"(d[21]), "+f"(d[22]), "+f"(d[23]), "+f"(d[24]), "+f"(d[25]), "+f"(d[26]), "+f"(d[27]), "+f"(d[28]), "+f"(d[29]), "+f"(d[30]), "+f"(d[31]), "+f"(d[32]), "+f"(d[33]), "+f"(d[34]), "+f"(d[35]), "+f"(d[36]), "+f"(d[37]), "+f"(d[38]), "+f"(d[39]), "+f"(d[40]), "+f"(d[41]), "+f"(d[42]), "+f"(d[43]), "+f"(d[44]), "+f"(d[45]), "+f"(d[46]), "+f"(d[47]), "+l"(a), "+l"(b)
    : "r"(ai), "r"(bi), "r"(sd), "n"(TA), "n"(TB));
}
template <int TA, int TB, int SZ>
__device__ __forceinline__ void wgmma_n128(float (&d)[SZ], uint64_t& a, int ai, uint64_t& b, int bi, int sd) {
  asm volatile("{ .reg .pred p; .reg .b32 l0, h0, l1, h1; setp.ne.b32 p, %68, 0;\n"
    "wgmma.mma_async.sync.aligned.m64n128k16.f32.bf16.bf16 {%0, %1, %2, %3, %4, %5, %6, %7, %8, %9, %10, %11, %12, %13, %14, %15, %16, %17, %18, %19, %20, %21, %22, %23, %24, %25, %26, %27, %28, %29, %30, %31, %32, %33, %34, %35, %36, %37, %38, %39, %40, %41, %42, %43, %44, %45, %46, %47, %48, %49, %50, %51, %52, %53, %54, %55, %56, %57, %58, %59, %60, %61, %62, %63}, %64, %65, p, 1, 1, %69, %70;\n"
    "mov.b64 {l0, h0}, %64; add.s32 l0, l0, %66; mov.b64 %64, {l0, h0};\n"
    "mov.b64 {l1, h1}, %65; add.s32 l1, l1, %67; mov.b64 %65, {l1, h1}; }"
    : "+f"(d[0]), "+f"(d[1]), "+f"(d[2]), "+f"(d[3]), "+f"(d[4]), "+f"(d[5]), "+f"(d[6]), "+f"(d[7]), "+f"(d[8]), "+f"(d[9]), "+f"(d[10]), "+f"(d[11]), "+f"(d[12]), "+f"(d[13]), "+f"(d[14]), "+f"(d[15]), "+f"(d[16]), "+f"(d[17]), "+f"(d[18]), "+f"(d[19]), "+f"(d[20]), "+f"(d[21]), "+f"(d[22]), "+f"(d[23]), "+f"(d[24]), "+f"(d[25]), "+f"(d[26]), "+f"(d[27]), "+f"(d[28]), "+f"(d[29]), "+f"(d[30]), "+f"(d[31]), "+f"(d[32]), "+f"(d[33]), "+f"(d[34]), "+f"(d[35]), "+f"(d[36]), "+f"(d[37]), "+f"(d[38]), "+f"(d[39]), "+f"(d[40]), "+f"(d[41]), "+f"(d[42]), "+f"(d[43]), "+f"(d[44]), "+f"(d[45]), "+f"(d[46]), "+f"(d[47]), "+f"(d[48]), "+f"(d[49]), "+f"(d[50]), "+f"(d[51]), "+f"(d[52]), "+f"(d[53]), "+f"(d[54]), "+f"(d[55]), "+f"(d[56]), "+f"(d[57]), "+f"(d[58]), "+f"(d[59]), "+f"(d[60]), "+f"(d[61]), "+f"(d[62]), "+f"(d[63]), "+l"(a), "+l"(b)
    : "r"(ai), "r"(bi), "r"(sd), "n"(TA), "n"(TB));
}
__device__ __forceinline__ void wgmma_rs_n32(float (&d)[64], const uint32_t* a, uint64_t b, uint64_t bo, int sd) {
  asm volatile("{ .reg .pred p; .reg .b64 db; setp.ne.b32 p, %22, 0; add.u64 db, %20, %21;\n"
    "wgmma.mma_async.sync.aligned.m64n32k16.f32.bf16.bf16 {%0, %1, %2, %3, %4, %5, %6, %7, %8, %9, %10, %11, %12, %13, %14, %15}, {%16, %17, %18, %19}, db, p, 1, 1, 0; }"
    : "+f"(d[48]), "+f"(d[49]), "+f"(d[50]), "+f"(d[51]), "+f"(d[52]), "+f"(d[53]), "+f"(d[54]), "+f"(d[55]), "+f"(d[56]), "+f"(d[57]), "+f"(d[58]), "+f"(d[59]), "+f"(d[60]), "+f"(d[61]), "+f"(d[62]), "+f"(d[63])
    : "r"(a[0]), "r"(a[1]), "r"(a[2]), "r"(a[3]), "l"(b), "l"(bo), "r"(sd));
}
__device__ __forceinline__ void wgmma_rs_n64(float (&d)[64], const uint32_t* a, uint64_t b, uint64_t bo, int sd) {
  asm volatile("{ .reg .pred p; .reg .b64 db; setp.ne.b32 p, %38, 0; add.u64 db, %36, %37;\n"
    "wgmma.mma_async.sync.aligned.m64n64k16.f32.bf16.bf16 {%0, %1, %2, %3, %4, %5, %6, %7, %8, %9, %10, %11, %12, %13, %14, %15, %16, %17, %18, %19, %20, %21, %22, %23, %24, %25, %26, %27, %28, %29, %30, %31}, {%32, %33, %34, %35}, db, p, 1, 1, 0; }"
    : "+f"(d[32]), "+f"(d[33]), "+f"(d[34]), "+f"(d[35]), "+f"(d[36]), "+f"(d[37]), "+f"(d[38]), "+f"(d[39]), "+f"(d[40]), "+f"(d[41]), "+f"(d[42]), "+f"(d[43]), "+f"(d[44]), "+f"(d[45]), "+f"(d[46]), "+f"(d[47]), "+f"(d[48]), "+f"(d[49]), "+f"(d[50]), "+f"(d[51]), "+f"(d[52]), "+f"(d[53]), "+f"(d[54]), "+f"(d[55]), "+f"(d[56]), "+f"(d[57]), "+f"(d[58]), "+f"(d[59]), "+f"(d[60]), "+f"(d[61]), "+f"(d[62]), "+f"(d[63])
    : "r"(a[0]), "r"(a[1]), "r"(a[2]), "r"(a[3]), "l"(b), "l"(bo), "r"(sd));
}
__device__ __forceinline__ void wgmma_rs_n96(float (&d)[64], const uint32_t* a, uint64_t b, uint64_t bo, int sd) {
  asm volatile("{ .reg .pred p; .reg .b64 db; setp.ne.b32 p, %54, 0; add.u64 db, %52, %53;\n"
    "wgmma.mma_async.sync.aligned.m64n96k16.f32.bf16.bf16 {%0, %1, %2, %3, %4, %5, %6, %7, %8, %9, %10, %11, %12, %13, %14, %15, %16, %17, %18, %19, %20, %21, %22, %23, %24, %25, %26, %27, %28, %29, %30, %31, %32, %33, %34, %35, %36, %37, %38, %39, %40, %41, %42, %43, %44, %45, %46, %47}, {%48, %49, %50, %51}, db, p, 1, 1, 0; }"
    : "+f"(d[16]), "+f"(d[17]), "+f"(d[18]), "+f"(d[19]), "+f"(d[20]), "+f"(d[21]), "+f"(d[22]), "+f"(d[23]), "+f"(d[24]), "+f"(d[25]), "+f"(d[26]), "+f"(d[27]), "+f"(d[28]), "+f"(d[29]), "+f"(d[30]), "+f"(d[31]), "+f"(d[32]), "+f"(d[33]), "+f"(d[34]), "+f"(d[35]), "+f"(d[36]), "+f"(d[37]), "+f"(d[38]), "+f"(d[39]), "+f"(d[40]), "+f"(d[41]), "+f"(d[42]), "+f"(d[43]), "+f"(d[44]), "+f"(d[45]), "+f"(d[46]), "+f"(d[47]), "+f"(d[48]), "+f"(d[49]), "+f"(d[50]), "+f"(d[51]), "+f"(d[52]), "+f"(d[53]), "+f"(d[54]), "+f"(d[55]), "+f"(d[56]), "+f"(d[57]), "+f"(d[58]), "+f"(d[59]), "+f"(d[60]), "+f"(d[61]), "+f"(d[62]), "+f"(d[63])
    : "r"(a[0]), "r"(a[1]), "r"(a[2]), "r"(a[3]), "l"(b), "l"(bo), "r"(sd));
}
__device__ __forceinline__ void wgmma_rs_n128(float (&d)[64], const uint32_t* a, uint64_t b, uint64_t bo, int sd) {
  asm volatile("{ .reg .pred p; .reg .b64 db; setp.ne.b32 p, %70, 0; add.u64 db, %68, %69;\n"
    "wgmma.mma_async.sync.aligned.m64n128k16.f32.bf16.bf16 {%0, %1, %2, %3, %4, %5, %6, %7, %8, %9, %10, %11, %12, %13, %14, %15, %16, %17, %18, %19, %20, %21, %22, %23, %24, %25, %26, %27, %28, %29, %30, %31, %32, %33, %34, %35, %36, %37, %38, %39, %40, %41, %42, %43, %44, %45, %46, %47, %48, %49, %50, %51, %52, %53, %54, %55, %56, %57, %58, %59, %60, %61, %62, %63}, {%64, %65, %66, %67}, db, p, 1, 1, 0; }"
    : "+f"(d[0]), "+f"(d[1]), "+f"(d[2]), "+f"(d[3]), "+f"(d[4]), "+f"(d[5]), "+f"(d[6]), "+f"(d[7]), "+f"(d[8]), "+f"(d[9]), "+f"(d[10]), "+f"(d[11]), "+f"(d[12]), "+f"(d[13]), "+f"(d[14]), "+f"(d[15]), "+f"(d[16]), "+f"(d[17]), "+f"(d[18]), "+f"(d[19]), "+f"(d[20]), "+f"(d[21]), "+f"(d[22]), "+f"(d[23]), "+f"(d[24]), "+f"(d[25]), "+f"(d[26]), "+f"(d[27]), "+f"(d[28]), "+f"(d[29]), "+f"(d[30]), "+f"(d[31]), "+f"(d[32]), "+f"(d[33]), "+f"(d[34]), "+f"(d[35]), "+f"(d[36]), "+f"(d[37]), "+f"(d[38]), "+f"(d[39]), "+f"(d[40]), "+f"(d[41]), "+f"(d[42]), "+f"(d[43]), "+f"(d[44]), "+f"(d[45]), "+f"(d[46]), "+f"(d[47]), "+f"(d[48]), "+f"(d[49]), "+f"(d[50]), "+f"(d[51]), "+f"(d[52]), "+f"(d[53]), "+f"(d[54]), "+f"(d[55]), "+f"(d[56]), "+f"(d[57]), "+f"(d[58]), "+f"(d[59]), "+f"(d[60]), "+f"(d[61]), "+f"(d[62]), "+f"(d[63])
    : "r"(a[0]), "r"(a[1]), "r"(a[2]), "r"(a[3]), "l"(b), "l"(bo), "r"(sd));
}

__device__ __forceinline__ void st_either(bool loc, uint32_t a, uint32_t x, uint32_t y, uint32_t z, uint32_t w, uint32_t bar) {
  if (loc) asm volatile("st.shared.v4.b32 [%0], {%1,%2,%3,%4};" :: "r"(a), "r"(x), "r"(y), "r"(z), "r"(w) : "memory");
  else st_async4(a, x, y, z, w, bar);
}
__device__ __forceinline__ void prep_task(bool loc, uint32_t src, uint32_t dst, uint32_t bar, uint32_t w0, uint32_t w1, uint32_t w2, uint32_t w3) {
  uint32_t k[12], u[9];
#pragma unroll
  for (int j = 0; j < 12; j++) k[j] = lds32(j < 4 ? src + (4 + j) * 528 - 16 : src + (j - 4) * 528);
#pragma unroll
  for (int j = 0; j < 9; j++) u[j] = lds32(j < 1 ? src + 4224 + 7 * 528 - 16 : src + 4224 + (j - 1) * 528);
#pragma unroll
  for (int j = 0; j < 9; j++) {
    uint32_t s = bmul(k[j], w3);
    s = bfma(k[j + 1], w2, s); s = bfma(k[j + 2], w1, s); s = bfma(k[j + 3], w0, s);
    u[j] = bmul(s, u[j]);
  }
#pragma unroll
  for (int c = 0; c < 2; c++) {
    const uint32_t sel = c ? 0x7632 : 0x5410;
    st_either(loc, dst + c * U_PITCH, __byte_perm(u[2], u[1], sel), __byte_perm(u[4], u[3], sel), __byte_perm(u[6], u[5], sel), __byte_perm(u[8], u[7], sel), bar);
    st_either(loc, dst + c * U_PITCH + U_ODD, __byte_perm(u[1], u[0], sel), __byte_perm(u[3], u[2], sel), __byte_perm(u[5], u[4], sel), __byte_perm(u[7], u[6], sel), bar);
  }
}

template <int S, int C0, int NK>
__device__ __forceinline__ void frag_load(uint32_t (&P)[4 * NK], uint32_t ua, uint32_t z) {
  P[2] = lds32(ua + 1024 * S + 32 * C0 - 16);
#pragma unroll
  for (int kk = 0; kk < NK; kk++) { P[4 * kk] = lds32(ua + 1024 * S + 32 * (C0 + kk)); P[4 * kk + 1] = lds32(ua + 1024 * S + 32 * (C0 + kk) + 16); }
#pragma unroll
  for (int kk = 0; kk < NK; kk++) { P[4 * kk + 3] = P[4 * kk] ^ z; if (kk) P[4 * kk + 2] = P[4 * kk - 3] ^ z; }
#pragma unroll
  for (int i = 0; i < 4 * NK; i++) asm volatile("" : "+r"(P[i]) :: "memory");
}
template <int S, int C0, int NK, int CH>
__device__ __forceinline__ void conv_issue(float (&acc)[64], const uint32_t (&P)[4 * NK], uint64_t& db, uint64_t z64) {
  if (S > 0 && C0 == 0) reg_rename<16 * S, 64>(acc);
  if (C0 == 0 && CH == 0) asm volatile("add.u64 %0, %0, %1;" : "+l"(db) : "l"(z64));
  wg_fence();
#pragma unroll
  for (int kk = 0; kk < NK; kk++) {
    const uint64_t o = 16 - 2 * (C0 + kk) + CH * (T_PITCH / 8);
    if (S == 0) wgmma_rs_n128(acc, &P[4 * kk], db, o, C0 + kk != 0);
    if (S == 1) wgmma_rs_n96(acc, &P[4 * kk], db, o, 1);
    if (S == 2) wgmma_rs_n64(acc, &P[4 * kk], db, o, 1);
    if (S == 3) wgmma_rs_n32(acc, &P[4 * kk], db, o, 1);
  }
  wg_commit();
}
template <int S>
__device__ __forceinline__ void conv_dump(float (&acc)[64], uint32_t xw, int wl) {
  reg_fence<16 * S, 16 * S + 16>(acc);
#pragma unroll
  for (int r = 0; r < 3; r++) {
    const int i = 16 * S + 4 * (r + 1);
    if (S < 3 || wl + r + 1 < 4) sts64(xw + (4 * S + r + 1) * 768 + r * 256, pack2(acc[i], acc[i + 1]), pack2(acc[i + 2], acc[i + 3]));
  }
}
template <int S>
__device__ __forceinline__ void conv_reduce(float (&y)[4], const float (&acc)[64], uint32_t xw, int wl) {
#pragma unroll
  for (int i = 0; i < 4; i++) y[i] = acc[16 * S + i];
#pragma unroll
  for (int r = 0; r < 3; r++) {
    uint2 v = make_uint2(0u, 0u);
    if (S > 0 || r < wl) v = lds64(xw + 4 * S * 768 + r * 256);
    y[0] += blo(v.x); y[1] += bhi(v.x); y[2] += blo(v.y); y[3] += bhi(v.y);
  }
}
struct FinCtx { uint32_t um, xt, st, DA, DB; uint32_t *hA, *hB; };
template <int S>
__device__ __forceinline__ void conv_z(uint32_t (&zz)[4], const FinCtx& c, const float (&aA)[64], const float (&aB)[64], uint32_t xA, uint32_t xB, int wl) {
  uint32_t u[4];
  float ya[4], yb[4];
  ldsm4t(c.um + S * 1024, u[0], u[1], u[2], u[3]);
  conv_reduce<S>(ya, aA, xA, wl); conv_reduce<S>(yb, aB, xB, wl);
  zz[0] = bfma(u[0], c.DA, pack2(ya[0], ya[1])); zz[1] = bfma(u[1], c.DA, pack2(ya[2], ya[3]));
  zz[2] = bfma(u[2], c.DB, pack2(yb[0], yb[1])); zz[3] = bfma(u[3], c.DB, pack2(yb[2], yb[3]));
}
template <int S>
__device__ __forceinline__ void conv_fin(const FinCtx& c, const uint32_t (&zz)[4]) {
  constexpr uint32_t XO = (S < 2 ? OFF_XTE : OFF_XTL) + (S & 1) * 4096, SO = (S < 2 ? OFF_STE : OFF_STL) + (S & 1) * 2048;
#pragma unroll
  for (int h = 0; h < 2; h++) {
    uint2 sv = lds64(c.st + SO + h * 256);
    uint32_t xa = lds32(c.xt + XO + h * 512), xb = lds32((c.xt ^ 64) + XO + h * 512);
    c.hA[(8 * S + h) * (D_ * 32)] = bfma(bfma(xa, sv.x, sv.y), zz[h], xa);
    c.hB[(8 * S + h) * (D_ * 32)] = bfma(bfma(xb, sv.x, sv.y), zz[2 + h], xb);
  }
}

struct RowC { float nm, k1, k2, hs; };
__device__ __forceinline__ float geglu(float g, float u, float cg, float cu, const RowC& r) {
  float gc = fmaf(r.nm, cg, g), uc = fmaf(r.nm, cu, u);
  float in = gc * fmaf(gc * gc, r.k2, r.k1);
  float t; asm("tanh.approx.f32 %0, %1;" : "=f"(t) : "f"(in));
  float pr = gc * uc;
  return fmaf(pr, t, pr);
}
template <int GI, int UI, int N>
__device__ __forceinline__ void epi_group(const float (&acc)[N], uint32_t cs, const RowC& r0, const RowC& r1, uint32_t* dst) {
  float4 c = lds128f(cs);
  uint32_t lo = pack2(geglu(acc[GI], acc[UI], c.x, c.z, r0), geglu(acc[GI + 1], acc[UI + 1], c.y, c.w, r0));
  uint32_t hi = pack2(geglu(acc[GI + 2], acc[UI + 2], c.x, c.z, r1), geglu(acc[GI + 3], acc[UI + 3], c.y, c.w, r1));
  dst[0] = lo; dst[32] = hi;
}

struct Params {
  const uint16_t *x, *shift_k, *ssm_k, *ssm_D, *wg, *wu, *wd;
  uint16_t* out;
  Scratch* scr;
  int i128, i64;
  uint64_t z64;
};

__global__ void __launch_bounds__(NTHR, 1)
fused_kernel(const Params p, const __grid_constant__ CUtensorMap tmXR, const __grid_constant__ CUtensorMap tmT, const __grid_constant__ CUtensorMap tmK, const __grid_constant__ CUtensorMap tmV,
             const __grid_constant__ CUtensorMap tmG, const __grid_constant__ CUtensorMap tmU,
             const __grid_constant__ CUtensorMap tmG32, const __grid_constant__ CUtensorMap tmU32,
             const __grid_constant__ CUtensorMap tmD, const __grid_constant__ CUtensorMap tmX) {
  extern __shared__ __align__(1024) uint8_t smem[];
  const uint32_t sb = s2u(smem);
  const uint32_t clk0 = clock();
  const int rank = blockIdx.x & 1, cl = blockIdx.x >> 1;
  const int q7 = ((cl - 36) * 37) >> 8, p8 = 4 + ((cl - 4) & 7) * 4 + ((cl - 4) >> 3), p7 = 4 * cl - 108 - 27 * q7;
  const int pair = cl < 4 ? cl : cl < 36 ? p8 : p7;
  const int bid = pair * 2 + rank;
  const int tile = bid >> 3, js = bid & 7;
  auto BAR = [&](int i) { return sb + OFF_BAR + i * 8; };
  auto kv_load = [&](int pc) {
    uint32_t b = BAR(B_KV + pc), d = sb + OFF_KV + pc * KV_PIECE;
    int run0 = pc * 64 + rank * 32 - 1;
    mbar_expect(b, KV_PIECE);
    tma3d(d, &tmK, pair * 8, run0, 0, b);
    tma3d(d + 4224, &tmV, pair * 8, run0, 0, b);
  };
  if (threadIdx.x < 32) {
    if (elect()) {
#pragma unroll
      for (int i = 0; i < 10; i++) mbar_init(BAR(40 + i), 1);
      mbar_expect(BAR(B_XR), 16384);
      asm volatile("cp.async.bulk.tensor.4d.shared::cluster.global.mbarrier::complete_tx::bytes [%0], [%1, {%3, %4, %5, %3}], [%2];"
                   :: "r"(sb + OFF_XR), "l"(&tmXR), "r"(BAR(B_XR)), "r"(0), "r"((bid & 7) * 2), "r"(bid & ~7) : "memory");
      kv_load(0);
#pragma unroll
      for (int i = 0; i < 2; i++) {
        mbar_expect(BAR(B_TAP + i), 2 * T_PITCH);
        tma3d(sb + OFF_TAP + i * 2 * T_PITCH, &tmT, 0, -1, bid * 4 + 2 * i, BAR(B_TAP + i));
      }
      SSTAMP(true, 26);
    }
    __syncwarp();
  }
  const int tid = (threadIdx.x + 384) & 511, lane = tid & 31;
  const int warp = __shfl_sync(0xffffffffu, tid >> 5, 0);
  const int g = lane >> 2, q = lane & 3;
  uint4 small;
  if (warp >= 8) {
    if (warp != 12 && elect()) {
      const int cnt = warp < 10 ? 8 : (warp < 12 ? 4 : 1), cnt0 = warp == 13 ? 5 : cnt;
#pragma unroll
      for (int i = 0; i < 10; i++) mbar_init(BAR((warp - 8) * 10 + i), i < 4 ? cnt0 : (warp == 9 ? 1 : cnt));
      asm volatile("fence.mbarrier_init.release.cluster;" ::: "memory");
      if (warp == 13) {
#pragma unroll
        for (int i = 0; i < 8; i++) mbar_expect(BAR(B_U + i), i < 4 ? 4096 : i < 6 ? 8192 : 512);
      }
    }
    __syncwarp();
    if (warp < 12) small = __ldg((const uint4*)(p.shift_k + (pair * 8 + 2 * q) * 4));
    else small.x = p.scr->epoch[bid];
  } else {
    const uint2 d4 = __ldg((const uint2*)(p.ssm_D + bid * 4));
    small.x = d4.x; small.y = d4.y;
    if (tid < 64) sts32(sb + OFF_U + (tid >> 4) * U_PITCH + ((tid >> 3) & 1) * U_ODD + (tid & 7) * 4, 0u);
  }
  __syncthreads();
  asm volatile("barrier.cluster.arrive.relaxed.aligned;" ::: "memory");
  SSTAMP(tid == 0, 13);

  if (warp < 8) {
    asm volatile("setmaxnreg.inc.sync.aligned.u32 208;");
    {
      mbar_wait(BAR(B_XR), 0);
      SSTAMP(tid == 0, 49);
      const int mi = lane >> 3, rho = lane & 7;
      const int t = (rho & 1) + 4 * (rho >> 1) + 2 * (mi & 1);
      const int xrow = 2 * (t & 7) + ((t >> 3) ^ 1);
      const uint32_t xa = sb + OFF_XR + warp * 2048 + xrow * 128 + (((mi >> 1) ^ (xrow & 7)) * 16);
      const uint32_t xo = sb + OFF_XST + warp * 2048 + (g ^ (bid & 3)) * 32 + q * 8;
#pragma unroll
      for (int i = 0; i < 4; i++) {
        uint32_t m0, m1, m2, m3;
        ldsm4t(xa ^ (i * 32), m0, m1, m2, m3);
        sts64(xo + i * 512, m0, m1);
        sts64(xo + i * 512 + 256, m2, m3);
      }
      const int r = tid >> 4;
      const uint32_t ra = sb + OFF_XR + (2 * (r & 7) + ((r >> 3) ^ 1)) * 128 + (mi & 1) * 2048 + rho * 16;
      float f[32];
#pragma unroll
      for (int i = 0; i < 4; i++) {
        uint4 v = lds128(ra + i * 4096);
        f[8 * i] = blo(v.x); f[8 * i + 1] = bhi(v.x); f[8 * i + 2] = blo(v.y); f[8 * i + 3] = bhi(v.y);
        f[8 * i + 4] = blo(v.z); f[8 * i + 5] = bhi(v.z); f[8 * i + 6] = blo(v.w); f[8 * i + 7] = bhi(v.w);
      }
      float sa = 0.f, sc = 0.f;
#pragma unroll
      for (int i = 0; i < 16; i++) { sa += f[2 * i]; sc += f[2 * i + 1]; }
      sa += sc;
#pragma unroll
      for (int o = 1; o < 16; o <<= 1) sa += __shfl_xor_sync(0xffffffffu, sa, o);
      const float mean = sa * (1.f / D_);
      float qa = 0.f, qc = 0.f;
#pragma unroll
      for (int i = 0; i < 16; i++) { float d0 = f[2 * i] - mean, d1 = f[2 * i + 1] - mean; qa = fmaf(d0, d0, qa); qc = fmaf(d1, d1, qc); }
      qa += qc;
#pragma unroll
      for (int o = 1; o < 16; o <<= 1) qa += __shfl_xor_sync(0xffffffffu, qa, o);
      const float rs = blo(pack2(rsqrtf(fmaf(qa, 1.f / D_, 1e-5f)), 0.f));
      const uint32_t me = pack2(rs, -mean * rs), ot = __shfl_xor_sync(0xffffffffu, me, 16);
      if (lane == 0) sts64(sb + OFF_CS + warp * 8, __byte_perm(me, ot, 0x5410), __byte_perm(me, ot, 0x7632));
      __syncwarp();
      if (lane == 0) mbar_arrive(BAR(B_SIGX));
      SSTAMP(tid == 0, 48);
    }
    const int hw = warp >> 2, wl = warp & 3;
    {
      const int chA = bid * 4 + hw, chB = chA + 2;
      const int ig = g ^ 1;
      const uint32_t uA = sb + OFF_U + hw * U_PITCH + ((ig & 1) ? 0 : U_ODD) + 32 + ((ig - 2 * q) >> 1) * 4 + wl * 256;
      const uint32_t uB = uA + 2 * U_PITCH;
      uint64_t dT = mkdesc(sb + OFF_TAP + hw * T_PITCH, 16, 256, 3);
      const uint32_t z = blockIdx.x >> 16;
      const uint32_t xA = sb + OFF_XCH + (hw * 32 + wl) * 768 + lane * 8, xB = xA + 16 * 768;
      FinCtx fc;
      fc.um = sb + OFF_U + (hw + 2 * (lane >> 4)) * U_PITCH + 32 + wl * 256 + (lane & 7) * 32 + ((lane >> 3) & 1) * 16;
      fc.xt = sb + wl * 1024 + (lane >> 3) * 128 + (hw ^ (lane >> 3)) * 32 + (lane & 7) * 4;
      fc.st = sb + wl * 512 + lane * 8;
      fc.DA = __byte_perm(small.x, 0, hw ? 0x3232 : 0x1010); fc.DB = __byte_perm(small.y, 0, hw ? 0x3232 : 0x1010);
      fc.hA = (uint32_t*)p.scr->hT + (size_t)wl * 2 * (D_ * 32) + chA * 32 + ((g ^ (chA & 7)) * 4) + q;
      fc.hB = (uint32_t*)p.scr->hT + (size_t)wl * 2 * (D_ * 32) + chB * 32 + ((g ^ (chB & 7)) * 4) + q;
      asm volatile("barrier.cluster.wait.aligned;" ::: "memory");
      auto tap_fix = [&](int i) {
        const uint32_t a = sb + OFF_TAP + (hw + 2 * i) * T_PITCH + 256 + ((tid & 127) >> 3) * 256 + 128 + (tid & 7) * 16;
        mbar_wait(BAR(B_TAP + i), 0);
        const uint4 v = lds128(a);
        __syncwarp();
        asm volatile("st.shared.v4.b32 [%0], {%1,%2,%3,%4};" :: "r"(a ^ 16), "r"(v.x), "r"(v.y), "r"(v.z), "r"(v.w) : "memory");
        fence_async_s();
        bar_sync(1 + hw, 128);
      };
      tap_fix(0);
      SSTAMP(tid == 0, 2);
      float aA[64], aB[64];
      uint32_t z0[4], z1[4];
      {
        uint32_t P[16], Q[16];
        mbar_wait_cluster(BAR(B_U + 0), 0);
        SSTAMP(tid == 0, 3);
        frag_load<0, 0, 4>(P, uA, z); conv_issue<0, 0, 4, 0>(aA, P, dT, p.z64);
        frag_load<0, 4, 4>(Q, uA, z); conv_issue<0, 4, 4, 0>(aA, Q, dT, p.z64);
        tap_fix(1);
        wg_wait<1>(); frag_load<0, 0, 4>(P, uB, z); conv_issue<0, 0, 4, 1>(aB, P, dT, p.z64);
        wg_wait<1>(); frag_load<0, 4, 4>(Q, uB, z); conv_issue<0, 4, 4, 1>(aB, Q, dT, p.z64);
        conv_dump<0>(aA, xA, wl);
        SSTAMP(tid == 0, 4);
        mbar_wait_cluster(BAR(B_U + 1), 0);
        SSTAMP(tid == 0, 5);
        wg_wait<1>(); frag_load<1, 0, 4>(P, uA, z); conv_issue<1, 0, 4, 0>(aA, P, dT, p.z64);
        wg_wait<1>(); frag_load<1, 4, 4>(Q, uA, z); conv_issue<1, 4, 4, 0>(aA, Q, dT, p.z64);
        conv_dump<0>(aB, xB, wl);
        wg_wait<1>(); frag_load<1, 0, 4>(P, uB, z); conv_issue<1, 0, 4, 1>(aB, P, dT, p.z64);
        bar_sync(1 + hw, 128);
        conv_z<0>(z0, fc, aA, aB, xA, xB, wl);
        wg_wait<1>(); frag_load<1, 4, 4>(Q, uB, z); conv_issue<1, 4, 4, 1>(aB, Q, dT, p.z64);
        conv_dump<1>(aA, xA, wl);
      }
      {
        uint32_t P[32], Q[32], R[32];
        SSTAMP(tid == 0, 6);
        mbar_wait_cluster(BAR(B_U + 2), 0);
        wg_wait<1>(); frag_load<2, 0, 8>(P, uA, z); conv_issue<2, 0, 8, 0>(aA, P, dT, p.z64);
        frag_load<2, 0, 8>(Q, uB, z); wg_wait<1>(); conv_issue<2, 0, 8, 1>(aB, Q, dT, p.z64);
        conv_dump<1>(aB, xB, wl);
        bar_sync(1 + hw, 128);
        conv_z<1>(z1, fc, aA, aB, xA, xB, wl);
        SSTAMP(tid == 0, 1);
        mbar_wait(BAR(B_XT), 0);
        SSTAMP(tid == 0, 7);
        conv_fin<0>(fc, z0);
        conv_fin<1>(fc, z1);
        __syncwarp();
        if (lane == 0) mbar_arrive(BAR(B_SIGE + 0));
        SSTAMP(tid == 0, 8);
        mbar_wait_cluster(BAR(B_U + 3), 0);
        frag_load<3, 0, 8>(R, uA, z); wg_wait<1>(); conv_issue<3, 0, 8, 0>(aA, R, dT, p.z64);
        frag_load<3, 0, 8>(P, uB, z); wg_wait<1>(); conv_issue<3, 0, 8, 1>(aB, P, dT, p.z64);
        SSTAMP(tid == 0, 9);
        conv_dump<2>(aA, xA, wl); conv_dump<2>(aB, xB, wl);
        wg_wait<0>();
        conv_dump<3>(aA, xA, wl); conv_dump<3>(aB, xB, wl);
        SSTAMP(tid == 0, 10);
        bar_sync(1 + hw, 128);
        mbar_wait(BAR(B_XT + 1), 0);
        SSTAMP(tid == 0, 11);
        conv_z<2>(z0, fc, aA, aB, xA, xB, wl);
        conv_fin<2>(fc, z0);
        conv_z<3>(z1, fc, aA, aB, xA, xB, wl);
        conv_fin<3>(fc, z1);
        __syncwarp();
        if (lane == 0) mbar_arrive(BAR(B_SIGE + 1));
        STAMP_IF(tid == 0, 12);
      }
    }
    const int blk = tile + 16 * hw;
    const uint32_t aw = sb + OFF_A + hw * 65536;
    const uint32_t fullA = BAR(B_FULLA + hw * 8), emptyA = BAR(B_EMPTYA + hw * 6);
    const uint32_t lmo = aw + (((lane >> 4) * 8 + (lane & 7)) * 128) + (((2 * wl + ((lane >> 3) & 1)) ^ (lane & 7)) * 16);
    uint64_t da = (mkdesc(aw, 0, 1024, 1) + p.z64), db = (mkdesc(sb + OFF_RING, 8192, 1024, 1) + p.z64);
    float acc1[64], acc2[64];
    RowC r0, r1;
    const int TS = 16 + hw * 16; (void)TS;

    {
      int slot = 0;
#pragma unroll 1
      for (int s = 0; s < 8; s++) {
        TW(twa, mbar_wait(fullA + s * 8, 0));
        STAMP_IF(wl == 0 && lane == 0 && s == 0, TS + 0);
        TW(twr, mbar_wait(BAR(B_FULLR + slot), s >= 6));
        wg_fence();
#pragma unroll
        for (int kk = 0; kk < 4; kk++) wgmma_n128<1, 1>(acc1, da, p.i128, db, kk < 3 ? p.i128 : (slot == 5 ? 640 - 6144 : 640), (s | kk) != 0);
        wg_commit();
        TW(twg, wg_wait<1>());
        if (lane == 0 && s > 0) mbar_arrive(BAR(B_EMPTYR + (slot == 0 ? 5 : slot - 1)));
        slot = slot == 5 ? 0 : slot + 1;
      }
    }
    STAMP_IF(wl == 0 && lane == 0, TS + 1);
    TWOUT(tid == 128, 1, twa); TWOUT(tid == 128, 2, twr); TWOUT(tid == 128, 3, twg);
    uint32_t* hdst = (uint32_t*)p.scr->H + (size_t)blk * (86 * 512) + wl * 64 + lane;
    const uint32_t csa = sb + OFF_CS + q * 16;
    da -= 4096;
#pragma unroll
    for (int s = 0; s < 8; s++) {
      constexpr int R0 = 8;
      const int r = R0 + s, slot = r % 6;
      TW(twr, mbar_wait(BAR(B_FULLR + slot), (r / 6) & 1));
      wg_fence();
#pragma unroll
      for (int kk = 0; kk < 4; kk++) wgmma_n128<1, 1>(acc2, da, s == 7 && kk == 3 ? 128 - 4096 : p.i128, db, kk < 3 ? p.i128 : (slot == 5 ? 640 - 6144 : 640), (s | kk) != 0);
      wg_commit();
      uint32_t* d = hdst + js * 8 * 256;
      if (s == 1) {
        reg_fence<0, 64>(acc1);
        TW(twa, mbar_wait_cluster(BAR(B_STX + hw), 0));
        auto mk = [](uint2 v) {
          const float rs = __uint_as_float(v.y), r2 = rs * rs;
          RowC r; r.nm = __uint_as_float(v.x); r.k1 = 0.7978845608028654f * rs; r.k2 = 0.044715f * r2 * r.k1; r.hs = 0.5f * r2;
          return r;
        };
        r0 = mk(lds64(sb + OFF_STX + warp * 128 + g * 8)); r1 = mk(lds64(sb + OFF_STX + warp * 128 + 64 + g * 8));
        TW(twa, mbar_wait(BAR(B_CS), 0));
        epi_group<0, 32>(acc1, csa + 0 * 64, r0, r1, d);
        epi_group<4, 36>(acc1, csa + 1 * 64, r0, r1, d + 256);
      }
      if (s == 2) { epi_group<8, 40>(acc1, csa + 2 * 64, r0, r1, d + 512); epi_group<12, 44>(acc1, csa + 3 * 64, r0, r1, d + 768); }
      if (s == 3) { epi_group<16, 48>(acc1, csa + 4 * 64, r0, r1, d + 1024); epi_group<20, 52>(acc1, csa + 5 * 64, r0, r1, d + 1280); }
      if (s == 4) { epi_group<24, 56>(acc1, csa + 6 * 64, r0, r1, d + 1536); epi_group<28, 60>(acc1, csa + 7 * 64, r0, r1, d + 1792);
                    __syncwarp(); if (lane == 0) mbar_arrive(BAR(B_SIGH + 0)); }
      TW(twg, wg_wait<1>());
      if (lane == 0) mbar_arrive(BAR(B_EMPTYR + (r - 1) % 6));
    }
    STAMP_IF(wl == 0 && lane == 0, TS + 2);
    TWOUT(tid == 128, 4, twa); TWOUT(tid == 128, 5, twr); TWOUT(tid == 128, 6, twg);
    db = (mkdesc(sb + OFF_RING + 4 * 16384, 4096, 512, 2) + p.z64);
    float acc3[48];
    uint32_t res[16];
#pragma unroll
    for (int s = 0; s < 8; s++) {
      constexpr int R0 = 16;
      const int r = R0 + s, slot = r % 6;
      TW(twr, mbar_wait(BAR(B_FULLR + slot), (r / 6) & 1));
      wg_fence();
#pragma unroll
      for (int kk = 0; kk < 4; kk++) wgmma_n96<1, 1>(acc3, da, p.i128, db, kk < 3 ? p.i64 : (slot == 5 ? 832 - 6144 : 832), (s | kk) != 0);
      wg_commit();
      uint32_t* d = hdst + (64 + js * 8) * 256;
      if (s == 0) {
#pragma unroll
        for (int kk = 0; kk < 4; kk++) ldsm4t(lmo + js * 8192 + kk * 2048, res[4 * kk], res[4 * kk + 1], res[4 * kk + 2], res[4 * kk + 3]);
        TW(twg, wg_wait<1>());
        if (lane == 0) mbar_arrive(BAR(B_EMPTYR + (r - 1) % 6));
        reg_fence<0, 64>(acc2);
        epi_group<0, 32>(acc2, csa + 8 * 64, r0, r1, d); epi_group<4, 36>(acc2, csa + 9 * 64, r0, r1, d + 256);
      }
      if (s == 1) { epi_group<8, 40>(acc2, csa + 10 * 64, r0, r1, d + 512); epi_group<12, 44>(acc2, csa + 11 * 64, r0, r1, d + 768); }
      if (s == 2) { epi_group<16, 48>(acc2, csa + 12 * 64, r0, r1, d + 1024); epi_group<20, 52>(acc2, csa + 13 * 64, r0, r1, d + 1280); }
      if (s == 3) { epi_group<24, 56>(acc2, csa + 14 * 64, r0, r1, d + 1536); epi_group<28, 60>(acc2, csa + 15 * 64, r0, r1, d + 1792);
                    __syncwarp(); if (lane == 0) mbar_arrive(BAR(B_SIGH + 1)); }
      if (s > 0) {
        TW(twg, wg_wait<1>());
        if (lane == 0) { mbar_arrive(BAR(B_EMPTYR + (r - 1) % 6)); if (s < 7) mbar_arrive(emptyA + (s - 1) * 8); }
      }
    }
    STAMP_IF(wl == 0 && lane == 0, TS + 3);
    TWOUT(tid == 128, 7, twa); TWOUT(tid == 128, 8, twr); TWOUT(tid == 128, 9, twg);
    da = (mkdesc(aw, 1024, 128, 0) + p.z64); db = (mkdesc(sb + OFF_RING, 8192, 1024, 1) + p.z64);
    float acco[64];
    {
      TW(twa, mbar_wait(fullA, 1));
      TW(twr, mbar_wait(BAR(B_FULLR), 0));
      wg_fence();
#pragma unroll
      for (int kk = 0; kk < 4; kk++) wgmma_n128<0, 1>(acco, da, p.i128, db, kk < 3 ? p.i128 : 640, kk != 0);
      wg_commit();
      TW(twg, wg_wait<1>());
      if (lane == 0) {
        mbar_arrive(BAR(B_EMPTYR + 23 % 6));
        asm volatile("mbarrier.arrive.relaxed.cluster.shared::cluster.b64 _, [%0];" :: "r"(mapa(BAR(B_PEER + hw), rank ^ 1)) : "memory");
      }
      reg_fence<0, 48>(acc3);
      uint32_t* d = hdst + (128 + js * 4) * 256;
      uint32_t* dx = hdst + (160 + js * 2) * 256;
      epi_group<0, 16>(acc3, csa + 16 * 64, r0, r1, d); epi_group<4, 20>(acc3, csa + 17 * 64, r0, r1, d + 256);
      epi_group<8, 24>(acc3, csa + 18 * 64, r0, r1, d + 512); epi_group<12, 28>(acc3, csa + 19 * 64, r0, r1, d + 768);
      if (js < 6) { epi_group<32, 40>(acc3, csa + 20 * 64, r0, r1, dx); epi_group<36, 44>(acc3, csa + 21 * 64, r0, r1, dx + 256); }
      __syncwarp();
      if (lane == 0) mbar_arrive(BAR(B_SIGH + 2));
      STAMP_IF(wl == 0 && lane == 0, TS + 4);
      int slot = 1;
#pragma unroll 1
      for (int s = 1; s < 8; s++) {
        TW(twa, mbar_wait(fullA + slot * 8, s < 6));
        TW(twr, mbar_wait(BAR(B_FULLR + slot), s >= 6));
        wg_fence();
#pragma unroll
        for (int kk = 0; kk < 4; kk++)
          wgmma_n128<0, 1>(acco, da, kk < 3 ? p.i128 : (slot == 5 ? 128 - 3072 : 128), db, kk < 3 ? p.i128 : (slot == 5 ? 640 - 6144 : 640), 1);
        wg_commit();
        TW(twg, wg_wait<1>());
        const int ps = slot == 0 ? 5 : slot - 1;
        if (lane == 0) { mbar_arrive(emptyA + ps * 8); mbar_arrive(BAR(B_EMPTYR + ps)); }
        slot = slot == 5 ? 0 : slot + 1;
        STAMP_IF(wl == 0 && lane == 0 && s == 4, TS + 5);
      }
    }
    wg_wait<0>();
    if (lane == 0) mbar_arrive(emptyA + 1 * 8);
    reg_fence<32, 64>(acco);
    reg_rename<0, 32>(acco);
    STAMP_IF(wl == 0 && lane == 0, TS + 6);
    TWOUT(tid == 128, 10, twa); TWOUT(tid == 128, 11, twr); TWOUT(tid == 128, 13, twg);
    float base[32];
    {
      mbar_wait_cluster(BAR(B_PEER + hw), 0);
      const uint32_t ra = mapa(aw + 6 * 8192 + wl * 4096 + lane * 16, rank ^ 1), rb = mapa(BAR(B_RECV + hw), rank ^ 1);
#pragma unroll
      for (int s = 8; s < 14; s++) {
        const int slot = s % 6, rs = 2 + ((s - 8) >> 1);
        if (s >= SEND_AT && s < SEND_AT + SEND_N) {
#pragma unroll
          for (int i = 4 / SEND_N * (s - SEND_AT); i < 4 / SEND_N * (s - SEND_AT + 1); i++)
            st_async4(ra + i * 512, pack2(acco[32 + 8 * i], acco[33 + 8 * i]), pack2(acco[34 + 8 * i], acco[35 + 8 * i]),
                      pack2(acco[36 + 8 * i], acco[37 + 8 * i]), pack2(acco[38 + 8 * i], acco[39 + 8 * i]), rb);
        }
        TW(twa, mbar_wait(fullA + slot * 8, (s / 6 + 1) & 1));
        if ((s & 1) == 0) TW(twr, mbar_wait(BAR(B_FULLR + rs), 1));
        STAMP_IF(wl == 0 && lane == 0 && s == 8, TS + 7);
        wg_fence();
#pragma unroll
        for (int kk = 0; kk < (s == 13 ? 2 : 4); kk++)
          wgmma_n64<0, 1>(acco, da, kk == 3 && slot == 5 ? 128 - 3072 : p.i128, db, p.i128, 1);
        wg_commit();
        if (s == BASE_AT) {
      mbar_wait_cluster(BAR(B_RECV + hw), 0);
      if (lane == 0) mbar_arrive(BAR(B_SIG + 6));
      STAMP_IF(tid == 0, 0);
#pragma unroll
      for (int i = 0; i < 4; i++) {
        const uint4 o = lds128(aw + 6 * 8192 + wl * 4096 + lane * 16 + i * 512);
        const uint32_t ov[4] = {o.x, o.y, o.z, o.w};
#pragma unroll
        for (int j = 0; j < 4; j++) {
          const float hs = (j & 1) ? r1.hs : r0.hs;
          base[8 * i + 2 * j] = fmaf(blo(ov[j]), hs, blo(res[4 * i + j])); base[8 * i + 2 * j + 1] = fmaf(bhi(ov[j]), hs, bhi(res[4 * i + j]));
        }
      }
      reg_fence<0, 32>(base);
        }
      }
    }
    {
      wg_wait<0>();
      reg_fence<0, 32>(acco);
      STAMP_IF(wl == 0 && lane == 0, TS + 8);
      TWOUT(tid == 128, 26, twa); TWOUT(tid == 128, 27, twr); TWOUT(tid == 128, 28, twg);
#pragma unroll
      for (int i = 0; i < 32; i++) acco[i] = fmaf(acco[i], (i & 2) ? r1.hs : r0.hs, base[i]);
      const uint32_t ob = aw + 6 * 8192 + wl * 4096 + 2048;
      const int row = (lane & 7) + ((lane >> 3) & 1) * 8;
#pragma unroll
      for (int i = 0; i < 4; i++) {
        int chunk = 2 * i + (lane >> 4);
        stsm4(ob + row * 128 + ((chunk ^ (row & 7)) * 16),
              pack2(acco[8 * i], acco[8 * i + 1]), pack2(acco[8 * i + 2], acco[8 * i + 3]),
              pack2(acco[8 * i + 4], acco[8 * i + 5]), pack2(acco[8 * i + 6], acco[8 * i + 7]));
      }
      __syncwarp();
#pragma unroll
      for (int i = 0; i < 4; i++) {
        int rr = i * 4 + (lane >> 3);
        uint4 v = lds128(ob + rr * 128 + (((lane & 7) ^ (rr & 7)) * 16));
        *(uint4*)(p.out + (size_t)tok(blk, wl * 16 + rr) * D_ + js * 64 + (lane & 7) * 8) = v;
      }
    }
    STAMP_IF(wl == 0 && lane == 0, TS + 9);
    STAMP_NS(tid == 0, 15);
  } else if (warp < 12) {
    asm volatile("setmaxnreg.dec.sync.aligned.u32 56;");
    const int h = warp - 8;
    const uint4 sk = small;
    const uint32_t w0 = __byte_perm(sk.x, sk.z, 0x5410), w1 = __byte_perm(sk.x, sk.z, 0x7632);
    const uint32_t w2 = __byte_perm(sk.y, sk.w, 0x5410), w3 = __byte_perm(sk.y, sk.w, 0x7632);
    const uint32_t psrc = sb + OFF_KV + 16 + lane * 4 + h * 128;
    const uint32_t pdst = mapa(sb + OFF_U + (q & 1) * 2 * U_PITCH + 32 + rank * 512 + g * 16 + h * 128, q >> 1), pbar = mapa(BAR(B_U), q >> 1);
    asm volatile("barrier.cluster.wait.aligned;" ::: "memory");
#pragma unroll 1
    for (int pc = 0; pc < 4; pc++) {
      mbar_wait(BAR(B_KV + pc), 0);
      SSTAMP(h == 0 && lane == 0, 42 + pc);
      prep_task((q >> 1) == rank, psrc + pc * KV_PIECE, pdst + pc * 1024, pbar + pc * 8, w0, w1, w2, w3);
      __syncwarp();
      if (lane == 0) mbar_arrive(BAR(B_U + pc));
      SSTAMP(h == 0 && lane == 0 && pc == 0, 27);
    }
    __syncwarp();
    if (lane == 0) mbar_arrive(BAR(B_PREPD));
    SSTAMP(h == 0 && lane == 0, 51);
    if (bid < 86) {
      const int which = bid >= 43, unit = bid - which * 43;
      uint32_t wa = sb + OFF_CW + h * 8192 + g * 64 + ((q ^ (g >> 1)) * 16);
      uint16_t* d = p.scr->wX + (size_t)((unit - 40) * 2 + (q >> 1)) * (D_ * 32) + (h * 128 + g) * 32 + ((which * 2 + (q & 1)) ^ (g >> 1)) * 8;
      float cs[8];
#pragma unroll
      for (int i = 0; i < 8; i++) cs[i] = 0.f;
      mbar_wait(BAR(B_CW), 0);
      mbar_wait(BAR(B_SIGE + 1), 0);
#pragma unroll 1
      for (int b = 0; b < 4; b++) {
        uint4 v[4];
#pragma unroll
        for (int i = 0; i < 4; i++) v[i] = lds128(wa + i * 512);
#pragma unroll
        for (int i = 0; i < 4; i++) {
          cs[0] += blo(v[i].x); cs[1] += bhi(v[i].x); cs[2] += blo(v[i].y); cs[3] += bhi(v[i].y);
          cs[4] += blo(v[i].z); cs[5] += bhi(v[i].z); cs[6] += blo(v[i].w); cs[7] += bhi(v[i].w);
        }
        if (unit >= 40) {
#pragma unroll
          for (int i = 0; i < 4; i++) *(uint4*)(d + i * 256) = v[i];
        }
        d += 1024; wa += 2048;
      }
#pragma unroll 1
      for (int o = 4; o < 32; o <<= 1)
#pragma unroll
        for (int i = 0; i < 8; i++) cs[i] += __shfl_xor_sync(0xffffffffu, cs[i], o);
      if (lane < 4) {
        sts128f(sb + OFF_CS + h * 128 + lane * 32, cs[0], cs[1], cs[2], cs[3]);
        sts128f(sb + OFF_CS + h * 128 + lane * 32 + 16, cs[4], cs[5], cs[6], cs[7]);
      }
      STAMP_IF(h == 0 && lane == 0, 53);
    }
    __syncwarp();
    if (lane == 0) mbar_arrive(BAR(B_CSD));
    const int ck = rank * 4 + h;
    const uint32_t sdst = mapa(sb + OFF_STX + (ck * 8 + g) * 8, q & 1), sbar = mapa(BAR(B_STX), q & 1);
#pragma unroll 1
    for (int w = 0; w < 2; w++) {
      uint32_t la = sb + OFF_A + w * 65536 + lane * 128 + ((ck ^ (lane & 7)) * 16);
      float s0 = 0.f, s1 = 0.f, q0 = 0.f, q1 = 0.f, c = 0.f;
#pragma unroll 1
      for (int s = 0; s < 8; s++) {
        uint32_t m[8];
        mbar_wait(BAR(B_FULLA + w * 8 + s), 0);
        ldsm4t(la, m[0], m[1], m[2], m[3]); ldsm4t(la + 4096, m[4], m[5], m[6], m[7]);
        la += 8192;
        if (STAT_SHIFT && s == 0) c = __shfl_sync(0xffffffffu, blo(m[0]), lane & ~3);
#pragma unroll
        for (int i = 0; i < 8; i++) {
          float d0 = blo(m[i]), d1 = bhi(m[i]);
          if (STAT_SHIFT) { d0 -= c; d1 -= c; }
          s0 += d0; s1 += d1; q0 = fmaf(d0, d0, q0); q1 = fmaf(d1, d1, q1);
        }
      }
      s0 += s1; q0 += q1;
#pragma unroll
      for (int o = 1; o < 4; o <<= 1) { s0 += __shfl_xor_sync(0xffffffffu, s0, o); q0 += __shfl_xor_sync(0xffffffffu, q0, o); }
      const float md = s0 * (1.f / D_), var = fmaxf(fmaf(-md, md, q0 * (1.f / D_)), 0.f);
      if (q < 2) asm volatile("st.async.weak.shared::cluster.mbarrier::complete_tx::bytes.v2.f32 [%0], {%1,%2}, [%3];"
                              :: "r"(sdst + w * 512), "f"(-(md + c)), "f"(rsqrtf(var + 1e-5f)), "r"(sbar + w * 8) : "memory");
      STAMP_IF(h == 0 && lane == 0, 46 + w);
    }
  } else {
    asm volatile("setmaxnreg.dec.sync.aligned.u32 40;");
    const int h = warp - 12;
    asm volatile("barrier.cluster.wait.aligned;" ::: "memory");
    if (h == 0) {
      if (elect()) {
#pragma unroll
        for (int pc = 1; pc < 4; pc++) {
          if (pc == KV_HOLD) mbar_wait(BAR(B_GO), 0);
          if (pc == 1 && KV_EVT) mbar_wait(BAR(B_XR), 0);
          if (pc == 2 && KV_EVT == 1) mbar_wait(BAR(B_KV), 0);
          if (pc == 2 && KV_EVT == 2) mbar_wait(BAR(B_TAP), 0);
          if (pc == 2 && KV_EVT == 3) mbar_wait(BAR(B_U), 0);
          if (pc == 1 && KV1_T) { while ((uint32_t)clock() - clk0 < KV1_T) {} }
          if (pc == 2 && KV2_T) { while ((uint32_t)clock() - clk0 < KV2_T) {} }
          if (pc == 3 && KV3_T) { while ((uint32_t)clock() - clk0 < KV3_T) {} }
          kv_load(pc);
        }
        const int cw = js * 64, c3 = 1024 + js * 32, co = cw ^ 64, kr = rank * 256, b3 = js < 6 ? 12288 : 8192;
        const uint16_t* wx = p.scr->wX + (size_t)js * (D_ * 32);
        mbar_wait(BAR(B_GO), 0);
        mbar_wait(BAR(B_KV + 3), 0);
        const uint16_t* hs0 = p.scr->H + (size_t)tile * (86 * 1024);
        const uint16_t* hp0 = hs0 + rank * 16384;
        static_for<0, SCHED_N>([&](auto ic) {
          constexpr int it = decltype(ic)::v, r = SCHED[it];
          if constexpr (r == 3) {
            if (bid < 86) {
              mbar_wait(BAR(B_PREPD), 0);
              fence_async_s();
              mbar_expect(BAR(B_CW), 32768);
#pragma unroll 1
              for (int i = 0; i < 8; i++) tma2d(sb + OFF_CW + i * 4096, bid >= 43 ? &tmU32 : &tmG32, (bid >= 43 ? bid - 43 : bid) * 32, i * 64, BAR(B_CW));
            }
            STAMP(28);
            mbar_wait(BAR(B_GO + 1), 0);
            fence_async_s();
            if (R_AFTER_A >= 0) mbar_wait(BAR(B_FULLA + R_AFTER_A), 0);
          }
          if constexpr (r == 10) asm volatile("cp.async.bulk.prefetch.L2.global [%0], %1;" :: "l"((const char*)p.wd + (size_t)bid * 11008), "r"(11008) : "memory");
          if constexpr (r == 16) mbar_wait(BAR(B_CS), 0);
          constexpr int w = r & 1, hs = (r - 64) >> 1;
          if constexpr (r >= 64) {
            if constexpr (w == 0 && (hs & 3) == 0 && hs < 12) { mbar_wait(BAR(B_SEEN + (hs >> 2)), 0); fence_async_g(); }
            mbar_wait(BAR(B_EMPTYA + w * 6 + hs % 6), (hs / 6) & 1);
          } else if constexpr (r >= 6) mbar_wait(BAR(B_EMPTYR + r % 6), (r / 6 - 1) & 1);
          static_for<SchedDep<it - 1>::v + 1, SchedDep<it>::v + 1>([&](auto jc) {
            constexpr int j = decltype(jc)::v, o = SCHED[j], os = (o - 64) >> 1;
            if constexpr (!SchedReused<j, it>::v) {
              if constexpr (o < 64) mbar_wait(BAR(B_FULLR + o % 6), (o / 6) & 1);
              else mbar_wait(BAR(B_FULLA + (o & 1) * 8 + os % 6), (os / 6 + 1) & 1);
            }
          });
          const uint32_t b = BAR(B_FULLR + r % 6), d = sb + OFF_RING + (r % 6) * 16384;
          if constexpr (r >= 64) {
            const uint32_t fb = BAR(B_FULLA + w * 8 + hs % 6);
            mbar_expect(fb, hs == 13 ? 4096 : 8192);
            bulk_ld(sb + OFF_A + w * 65536 + (hs % 6) * 8192,
                    (hs < 8 ? hp0 + ((hs & 4) * 2 + (hs & 3)) * 4096 : hs0 + (hs + 8) * 4096) + (size_t)w * (16 * 86 * 1024), hs == 13 ? 4096 : 8192, fb);
          } else if constexpr (r < 16) {
            mbar_expect(b, 16384);
            tma2d(d, &tmG, cw + (r >> 3) * 512, (r & 7) * 64, b); tma2d(d + 8192, &tmU, cw + (r >> 3) * 512, (r & 7) * 64, b);
          } else if constexpr (r < 24) {
            mbar_expect(b, b3);
            tma2d(d, &tmG32, c3, (r & 7) * 64, b); tma2d(d + 4096, &tmU32, c3, (r & 7) * 64, b);
            if (js < 6) bulk_ld(d + 8192, wx + (r & 7) * 2048, 4096, b);
          } else if constexpr (r < 32) {
            const int k = kr + ((r & 4) * 2 + (r & 3)) * 64;
            mbar_expect(b, 16384);
            tma2d(d, &tmD, cw, k, b); tma2d(d + 8192, &tmD, co, k, b);
          } else {
            mbar_expect(b, 16384);
            tma2d(d, &tmD, cw, 1024 + (r - 32) * 128, b); tma2d(d + 8192, &tmD, cw, 1088 + (r - 32) * 128, b);
          }
        });
        p.scr->epoch[bid] = small.x + 1;
      }
    } else if (h == 3) {
#pragma unroll 1
      for (int i = 0; i < 7; i++) {
        mbar_wait_bounded(BAR(B_SIG + i), 0);
        if (i == 6) break;
        unsigned* c = &p.scr->cnt[(i < 3 ? i : CNT_H + tile * 3 + i - 3) * 32];
        if (i == 0) {
          fence_async_s();
          if (elect()) {
            asm volatile("cp.async.bulk.tensor.2d.global.shared::cta.bulk_group [%0, {%2, %3}], [%1];" :: "l"(&tmX), "r"(sb + OFF_XST), "r"(bid * 64), "r"(0) : "memory");
            asm volatile("cp.async.bulk.global.shared::cta.bulk_group [%0], [%1], 64;" :: "l"(p.scr->st1 + bid * 16), "r"(sb + OFF_CS) : "memory");
            asm volatile("cp.async.bulk.commit_group;" ::: "memory");
            asm volatile("cp.async.bulk.wait_group 0;" ::: "memory");
          }
          __syncwarp();
        }
        if (lane == 0) { signal_gpu(c); if (i == 0 || i == 2) mbar_arrive(BAR(B_GO + (i >> 1))); }
        __syncwarp();
        STAMP_IF(lane == 0, i == 0 ? 50 : 53 + i);
        if (i == 2 && bid < 86) {
          const int which = bid >= 43, f = (bid - which * 43) * 32 + lane;
          mbar_wait_bounded(BAR(B_CSD), 0);
          const uint32_t a = sb + OFF_CS + lane * 4;
          p.scr->cs[(f >> 1) * 4 + which * 2 + (f & 1)] = __uint_as_float(lds32(a)) + __uint_as_float(lds32(a + 128)) + __uint_as_float(lds32(a + 256)) + __uint_as_float(lds32(a + 384));
          __syncwarp();
          if (lane == 0) signal_gpu(&p.scr->cnt[CNT_C * 32]);
          __syncwarp();
          STAMP_IF(lane == 0, 29);
        }
      }
    } else {
      const unsigned ep = small.x + 1;
      const int w = h - 1, blk = tile + 16 * w;
      const uint32_t aw = sb + OFF_A + w * 65536;
      const uint32_t fullA = BAR(B_FULLA + w * 8);
      if (elect()) {
        if (w == 0) {
          mbar_wait(BAR(B_GO), 0);
          poll1(&p.scr->cnt[CNT_X * 32], ep * NCTA);
          fence_async_g(); fence_async_s();
          uint32_t b = BAR(B_XT);
          mbar_expect(b, 12288); mbar_expect(b + 8, 12288);
          bulk_ld(sb + OFF_XTE, p.scr->xT + (size_t)bid * 8192, 8192, b);
          bulk_ld(sb + OFF_STE, p.scr->st1, 4096, b);
          bulk_ld(sb + OFF_XTL, p.scr->xT + (size_t)bid * 8192 + 4096, 8192, b + 8);
          bulk_ld(sb + OFF_STL, p.scr->st1 + 1024, 4096, b + 8);
          SSTAMP(true, 52);
        }
      const uint16_t* asrc = p.scr->hT + (size_t)blk * (D_ * 64);
      const unsigned* hc = &p.scr->cnt[(CNT_H + tile * 3) * 32];
        mbar_wait(w ? BAR(B_GO + 1) : BAR(B_SIGE), 0);
        fence_async_s();
        poll1(&p.scr->cnt[(CNT_E + w) * 32], ep * NCTA);
        STAMP(59 + w);
        if (A_AFTER_GO) mbar_wait(BAR(B_GO + 1), 0);
        fence_async_g();
#pragma unroll
        for (int s = 0; s < 8; s++) {
          if (s == 3 && w == 0) { mbar_wait(BAR(B_CSD), 0); fence_async_s(); }
          if (s >= A_DEPTH0 && w == 0) mbar_wait(fullA + (s - A_DEPTH0) * 8, 0);
          if (s >= A_DEPTH && w == 1) mbar_wait(fullA + (s - A_DEPTH) * 8, 0);
          mbar_expect(fullA + s * 8, 8192);
          bulk_ld(aw + s * 8192, asrc + s * 4096, 8192, fullA + s * 8);
        }
        if (w == 0) {
          poll1(&p.scr->cnt[CNT_C * 32], ep * 86);
          fence_async_g(); fence_async_s();
          uint32_t b = BAR(B_CS), d = sb + OFF_CS;
          mbar_expect(b, js < 6 ? 1408 : 1280);
          bulk_ld(d, p.scr->cs + js * 128, 512, b);
          bulk_ld(d + 512, p.scr->cs + 1024 + js * 128, 512, b);
          bulk_ld(d + 1024, p.scr->cs + 2048 + js * 64, 256, b);
          if (js < 6) bulk_ld(d + 1280, p.scr->cs + 2560 + js * 32, 128, b);
          STAMP(30);
        }
        if (w == 1) {
#pragma unroll 1
          for (int c = 0; c < 3; c++) {
            mbar_wait(BAR(B_SIGH + c), 0);
            poll1(hc + c * 32, ep * 8);
            mbar_arrive(BAR(B_SEEN + c));
            STAMP(61 + c);
          }
        }
      }
    }
  }
}

typedef CUresult (*EncFn)(CUtensorMap*, CUtensorMapDataType, cuuint32_t, void*, const cuuint64_t*, const cuuint64_t*,
                          const cuuint32_t*, const cuuint32_t*, CUtensorMapInterleave, CUtensorMapSwizzle,
                          CUtensorMapL2promotion, CUtensorMapFloatOOBfill);

void make_map(EncFn fn, CUtensorMap* tm, const void* ptr, int w, int hgt, int bw, int bh, CUtensorMapSwizzle sw, CUtensorMapL2promotion pr) {
  cuuint64_t dims[2] = {(cuuint64_t)w, (cuuint64_t)hgt};
  cuuint64_t str[1] = {(cuuint64_t)w * 2};
  cuuint32_t box[2] = {(cuuint32_t)bw, (cuuint32_t)bh}, es[2] = {1, 1};
  fn(tm, CU_TENSOR_MAP_DATA_TYPE_BFLOAT16, 2, (void*)ptr, dims, str, box, es, CU_TENSOR_MAP_INTERLEAVE_NONE, sw, pr,
     CU_TENSOR_MAP_FLOAT_OOB_FILL_NONE);
}

void make_map_runs(EncFn fn, CUtensorMap* tm, const void* ptr) {
  cuuint64_t dims[3] = {(cuuint64_t)D_, (cuuint64_t)(S_ / 8), 8};
  cuuint64_t str[2] = {(cuuint64_t)D_ * 16, (cuuint64_t)D_ * 2};
  cuuint32_t box[3] = {8, 33, 8}, es[3] = {1, 1, 1};
  fn(tm, CU_TENSOR_MAP_DATA_TYPE_BFLOAT16, 3, (void*)ptr, dims, str, box, es, CU_TENSOR_MAP_INTERLEAVE_NONE,
     CU_TENSOR_MAP_SWIZZLE_NONE, CU_TENSOR_MAP_L2_PROMOTION_L2_128B, CU_TENSOR_MAP_FLOAT_OOB_FILL_NONE);
}

}

extern "C" void kernel_launch(void* const* d_in, const int* in_sizes, int n_in, void* d_out, int out_size) {
  (void)in_sizes; (void)n_in; (void)out_size;
  static EncFn fn = nullptr;
  if (!fn) {
    void* f = nullptr; cudaDriverEntryPointQueryResult qr;
    cudaGetDriverEntryPoint("cuTensorMapEncodeTiled", &f, cudaEnableDefault, &qr);
    fn = (EncFn)f;
    cudaFuncSetAttribute(fused_kernel, cudaFuncAttributeMaxDynamicSharedMemorySize, SMEM_BYTES);
  }
  CUtensorMap tmK, tmV, tmG, tmU, tmG32, tmU32, tmD, tmX, tmXR, tmT;
  void* xT = nullptr;
  cudaGetSymbolAddress(&xT, g_scr);
  make_map(fn, &tmX, xT, 8192, 128, 64, 128, CU_TENSOR_MAP_SWIZZLE_NONE, CU_TENSOR_MAP_L2_PROMOTION_NONE);
  {
    cuuint64_t dims[3] = {128, 16, (cuuint64_t)D_}, str[2] = {256, (cuuint64_t)S_ * 2};
    cuuint32_t box[3] = {128, 17, 2}, es[4] = {1, 1, 1, 1};
    fn(&tmT, CU_TENSOR_MAP_DATA_TYPE_BFLOAT16, 3, d_in[4], dims, str, box, es, CU_TENSOR_MAP_INTERLEAVE_NONE,
       CU_TENSOR_MAP_SWIZZLE_NONE, CU_TENSOR_MAP_L2_PROMOTION_NONE, CU_TENSOR_MAP_FLOAT_OOB_FILL_NONE);
    cuuint64_t dims4[4] = {64, 16, 128, 8}, str4[3] = {1024, 16384, 128};
    cuuint32_t box4[4] = {64, 2, 8, 8};
    fn(&tmXR, CU_TENSOR_MAP_DATA_TYPE_BFLOAT16, 4, d_in[0], dims4, str4, box4, es, CU_TENSOR_MAP_INTERLEAVE_NONE,
       CU_TENSOR_MAP_SWIZZLE_128B, CU_TENSOR_MAP_L2_PROMOTION_L2_256B, CU_TENSOR_MAP_FLOAT_OOB_FILL_NONE);
  }
  make_map_runs(fn, &tmK, d_in[1]);
  make_map_runs(fn, &tmV, d_in[2]);
  make_map(fn, &tmG, d_in[7], F_, D_, 64, 64, CU_TENSOR_MAP_SWIZZLE_128B, CU_TENSOR_MAP_L2_PROMOTION_NONE);
  make_map(fn, &tmU, d_in[8], F_, D_, 64, 64, CU_TENSOR_MAP_SWIZZLE_128B, CU_TENSOR_MAP_L2_PROMOTION_NONE);
  make_map(fn, &tmG32, d_in[7], F_, D_, 32, 64, CU_TENSOR_MAP_SWIZZLE_64B, CU_TENSOR_MAP_L2_PROMOTION_NONE);
  make_map(fn, &tmU32, d_in[8], F_, D_, 32, 64, CU_TENSOR_MAP_SWIZZLE_64B, CU_TENSOR_MAP_L2_PROMOTION_NONE);
  make_map(fn, &tmD, d_in[9], D_, F_, 64, 64, CU_TENSOR_MAP_SWIZZLE_128B, CU_TENSOR_MAP_L2_PROMOTION_NONE);
  Params p;
  p.x = (const uint16_t*)d_in[0]; p.shift_k = (const uint16_t*)d_in[3]; p.ssm_k = (const uint16_t*)d_in[4];
  p.ssm_D = (const uint16_t*)d_in[5]; p.wg = (const uint16_t*)d_in[7]; p.wu = (const uint16_t*)d_in[8];
  p.wd = (const uint16_t*)d_in[9]; p.out = (uint16_t*)d_out; p.scr = (Scratch*)xT; p.i128 = 128; p.i64 = 64; p.z64 = 0;
  cudaLaunchConfig_t cfg = {};
  cfg.gridDim = dim3(NCTA); cfg.blockDim = dim3(NTHR); cfg.dynamicSmemBytes = SMEM_BYTES; cfg.stream = cudaStreamPerThread;
  cudaLaunchAttribute at[1];
  at[0].id = cudaLaunchAttributeClusterDimension; at[0].val.clusterDim.x = 2; at[0].val.clusterDim.y = 1; at[0].val.clusterDim.z = 1;
  cfg.attrs = at; cfg.numAttrs = 1;
  cudaLaunchKernelEx(&cfg, fused_kernel, p, tmXR, tmT, tmK, tmV, tmG, tmU, tmG32, tmU32, tmD, tmX);
}
```

```cpp
#include <cuda_runtime.h>
#include <cuda_bf16.h>
#include <cuda.h>
#include <stdint.h>

namespace {

constexpr int S_ = 2048, D_ = 512, F_ = 1376;
constexpr int NCTA = 128, NTHR = 512;
#define FFN_MAP 0
#define STAT_SHIFT 0
#define CONV_ORDER 0
#define CONV_TAIL 0
#define PREP_FMA 1
#define KV_EVT 2
#define A_AFTER_GO 0
#define A_DEPTH0 4
#define R_AFTER_A 1
#define WIN 72
#define WIN3 200
#define BASE_AT 13
#define ORD 2
#define W3_FROM 50
#define W2_FROM 36
#define WINA WIN
#define WARM 1
#define RED_H2 0
#define OUT_TMA 0
#define XS_BEFORE 0
#define KV3_EVT 0
#define X_SPLIT 0
#define WHATIF 0
#define CS_MODE 1
#define RES_EARLY 1
#define CS_PACK 1
#define WIN0 32
#define WINE 32
#define WINC 36
#define WE_TO 6
#define PF_W 0
#define PF_D 10
#define PRE_EVT 0
#define CW_AT 3
#define R3_EVT 0
#define CS_EVT 1
#define FRONT_ORD 0
#define X_WARP 0
#define TM_PF 0
#define SIG2 1
#define REG_C 216
#define REG_P 48
#define STX_AT 0
#define SEND_AT 8
#define SEND_N 2
#define GPC_MAP 1
#define KV_HOLD 0

#define A_DEPTH 2
#define WIN1 36

struct __align__(1024) Scratch {
  uint16_t xT[D_ * S_];
  uint16_t hT[32 * D_ * 64];
  uint16_t H[32 * 86 * 1024];
  uint16_t wX[6 * D_ * 32];
  uint32_t st1[S_];
  float    cs[F_ * 2];
  unsigned cnt[(4 + 48) * 32];
  unsigned epoch[NCTA];
};
__device__ Scratch g_scr;
#define STAMP(id)
#define STAMP_IF(c, id)
#define SSTAMP(c, id)
#define STAMP_NS(c, id)
constexpr int CNT_X = 0, CNT_E = 1, CNT_C = 3, CNT_H = 4;
__host__ __device__ constexpr int tok(int b, int tau) { return 128 * (b >> 1) + 16 * (tau & 7) + 8 * (b & 1) + ((tau >> 3) ^ 1); }

constexpr uint32_t OFF_A    = 0;
constexpr uint32_t OFF_RING = 131072;
constexpr uint32_t OFF_CS   = 229376;
constexpr uint32_t OFF_BAR  = OFF_CS + 1408;
constexpr uint32_t OFF_STX  = OFF_BAR + 640;
constexpr uint32_t SMEM_BYTES = 232448;
constexpr uint32_t KV_PIECE = 8448;
constexpr uint32_t OFF_KV   = 65536 - 4 * KV_PIECE;
constexpr uint32_t OFF_CW   = 32768;
constexpr uint32_t OFF_XR   = 0;
constexpr uint32_t OFF_XTE  = OFF_XR;
constexpr uint32_t OFF_STE  = OFF_XR + 8192;
constexpr uint32_t U_PITCH  = 8352, U_ODD = 4160;
constexpr uint32_t T_PITCH  = 4352;
constexpr uint32_t OFF_TAP  = 65536;
constexpr uint32_t OFF_U    = OFF_TAP + 4 * T_PITCH;
constexpr uint32_t OFF_XTL  = OFF_U + 4 * U_PITCH;
constexpr uint32_t OFF_STL  = OFF_XTL + 8192;
constexpr uint32_t OFF_XST  = OFF_RING + 2 * 16384;
constexpr uint32_t OFF_XCH  = OFF_RING + 3 * 16384;
static_assert(OFF_XR % 1024 == 0 && OFF_XR + 16384 <= 65536, "");
static_assert(OFF_STL + 4096 <= 131072, "");
static_assert(OFF_STX + 1024 <= SMEM_BYTES, "");
constexpr int B_EMPTYR = 0  , B_SIG = 6  , B_SIGT = 13,
              B_EMPTYA = 20  , B_PEER = 32  , B_PREPD = 34, B_CSD = 35, B_XSI = 39  ,
              B_KV = 40  , B_XR = 44, B_TAP = 45  , B_CS = 47, B_GO = 48  ,
              B_U = 50  , B_RECV = 54  , B_STX = 56  , B_XT = 58  , B_FULLA = 60  , B_CW = 76, B_SEEN = 77  ,
              B_FULLR = 14  ;
constexpr int B_SIGX = B_SIG, B_SIGE = B_SIG + 1, B_SIGH = B_SIG + 3;

#define HH(s) 64 + 2 * (s), 65 + 2 * (s)
constexpr int SCHED_N = 22 + 13 + 28;
constexpr int SCHED[SCHED_N] = {0, 1, 2, 3, 4, 5, 6, 7, 8, 9, 10, 11, 12, 13, 14, 15, 16, 17, 18, 19, 20, 21,
  22, HH(0), 23, HH(1), 24, HH(2), 25, HH(3), 26, 27, 28, 29, 30, HH(4), HH(5), HH(6), 31, HH(7), 32,
  HH(8), HH(9), 33, HH(10), HH(11), 34, HH(12), HH(13)};
constexpr int sched_kb(int v) { return v >= 64 ? 8 : v >= 16 && v < 24 ? 12 : 16; }
constexpr int sched_dep(int i) {
  int best = -1;
  for (int k = 0; k <= i; k++) {
    int acc = 0, win = k < 3 ? WIN0 : k < WE_TO ? WINE : k < 16 ? WIN1 : k < 22 ? WINC : (k >= W3_FROM ? WIN3 : k >= W2_FROM ? WIN : WINA);
    for (int j = k; j >= 0; j--) { acc += sched_kb(SCHED[j]); if (acc > win) { if (j > best) best = j; break; } }
  }
  return best;
}
constexpr bool sched_reused(int j, int i) {
  for (int k = j + 1; k <= i; k++) if (SCHED[k] == SCHED[j] + (SCHED[j] < 64 ? 6 : 12)) return true;
  return false;
}
template <int I> struct SchedDep { static constexpr int v = sched_dep(I); };
template <int J, int I> struct SchedReused { static constexpr bool v = sched_reused(J, I); };
template <int I> struct IC { static constexpr int v = I; };
template <int I, int E, class F> __device__ __forceinline__ void static_for(F&& f) { if constexpr (I < E) { f(IC<I>{}); static_for<I + 1, E>(f); } }

__device__ __forceinline__ uint32_t s2u(const void* p) { return (uint32_t)__cvta_generic_to_shared(p); }
__device__ __forceinline__ void mbar_init(uint32_t b, int n) { asm volatile("mbarrier.init.shared::cta.b64 [%0], %1;" :: "r"(b), "r"(n) : "memory"); }
__device__ __forceinline__ void mbar_expect(uint32_t b, int bytes) { asm volatile("mbarrier.arrive.expect_tx.shared::cta.b64 _, [%0], %1;" :: "r"(b), "r"(bytes) : "memory"); }
__device__ __forceinline__ void mbar_arrive(uint32_t b) { asm volatile("mbarrier.arrive.shared::cta.b64 _, [%0];" :: "r"(b) : "memory"); }
#define MBAR_WAIT_ASM(SEM) \
  asm volatile("{\n .reg .pred p;\nSPIN:\n mbarrier.try_wait.parity" SEM ".shared::cta.b64 p, [%0], %1;\n @!p bra SPIN;\n}" :: "r"(b), "r"(par) : "memory")
__device__ __forceinline__ void mbar_wait(uint32_t b, int par) { MBAR_WAIT_ASM(""); }
__device__ __forceinline__ void mbar_wait_cluster(uint32_t b, int par) {
  MBAR_WAIT_ASM("");
  asm volatile("fence.acquire.sync_restrict::shared::cluster.cluster;" ::: "memory");
}
__device__ __forceinline__ void mbar_wait_bounded(uint32_t b, int par) {
  asm volatile("{\n .reg .pred p, t; .reg .u32 c;\n mov.u32 c, 0;\n"
    "SPIN:\n mbarrier.try_wait.parity.shared::cta.b64 p, [%0], %1;\n @p bra DONE;\n"
    " add.u32 c, c, 1;\n setp.lt.u32 t, c, 1048576;\n @t bra SPIN;\n trap;\nDONE:\n}" :: "r"(b), "r"(par) : "memory");
}
__device__ __forceinline__ uint32_t mapa(uint32_t a, int r) { uint32_t d; asm("mapa.shared::cluster.u32 %0, %1, %2;" : "=r"(d) : "r"(a), "r"(r)); return d; }
__device__ __forceinline__ void st_async4(uint32_t a, uint32_t x, uint32_t y, uint32_t z, uint32_t w, uint32_t bar) {
  asm volatile("st.async.weak.shared::cluster.mbarrier::complete_tx::bytes.v4.b32 [%0], {%1,%2,%3,%4}, [%5];" :: "r"(a), "r"(x), "r"(y), "r"(z), "r"(w), "r"(bar) : "memory");
}
__device__ __forceinline__ void tma3d(uint32_t dst, const CUtensorMap* tm, int c0, int c1, int c2, uint32_t bar) {
  asm volatile("cp.async.bulk.tensor.3d.shared::cluster.global.mbarrier::complete_tx::bytes [%0], [%1, {%3, %4, %5}], [%2];" :: "r"(dst), "l"(tm), "r"(bar), "r"(c0), "r"(c1), "r"(c2) : "memory");
}
__device__ __forceinline__ void sts64(uint32_t a, uint32_t x, uint32_t y) { asm volatile("st.shared.v2.b32 [%0], {%1,%2};" :: "r"(a), "r"(x), "r"(y) : "memory"); }
__device__ __forceinline__ bool elect() { uint32_t p; asm volatile("{ .reg .pred P; elect.sync _|P, 0xffffffff; selp.u32 %0, 1, 0, P; }" : "=r"(p)); return p; }
__device__ __forceinline__ void bulk_ld(uint32_t dst, const void* src, int bytes, uint32_t bar) {
  asm volatile("cp.async.bulk.shared::cluster.global.mbarrier::complete_tx::bytes [%0], [%1], %2, [%3];" :: "r"(dst), "l"(src), "r"(bytes), "r"(bar) : "memory");
}
__device__ __forceinline__ void tma2d(uint32_t dst, const CUtensorMap* tm, int c0, int c1, uint32_t bar) {
  asm volatile("cp.async.bulk.tensor.2d.shared::cluster.global.mbarrier::complete_tx::bytes [%0], [%1, {%3, %4}], [%2];" :: "r"(dst), "l"(tm), "r"(bar), "r"(c0), "r"(c1) : "memory");
}
__device__ __forceinline__ void fence_async_g() { asm volatile("fence.proxy.async.global;" ::: "memory"); }
__device__ __forceinline__ void fence_async_s() { asm volatile("fence.proxy.async.shared::cta;" ::: "memory"); }
__device__ __forceinline__ void poll1(const unsigned* p, unsigned target) {
  unsigned v;
  do { asm volatile("ld.relaxed.gpu.global.u32 %0, [%1];" : "=r"(v) : "l"(p) : "memory"); } while ((int)(v - target) < 0);
  asm volatile("fence.acquire.gpu;" ::: "memory");
}
__device__ __forceinline__ void signal_gpu(unsigned* p) {
  fence_async_g();
  asm volatile("red.release.gpu.global.add.u32 [%0], 1;" :: "l"(p) : "memory");
}
__device__ __forceinline__ void bar_sync(int id, int n) { asm volatile("bar.sync %0, %1;" :: "r"(id), "r"(n) : "memory"); }
__device__ __forceinline__ uint32_t lds32(uint32_t a) { uint32_t v; asm volatile("ld.shared.b32 %0, [%1];" : "=r"(v) : "r"(a)); return v; }
__device__ __forceinline__ uint2 lds64(uint32_t a) { uint2 v; asm volatile("ld.shared.v2.b32 {%0,%1}, [%2];" : "=r"(v.x), "=r"(v.y) : "r"(a)); return v; }
__device__ __forceinline__ uint4 lds128(uint32_t a) { uint4 v; asm volatile("ld.shared.v4.b32 {%0,%1,%2,%3}, [%4];" : "=r"(v.x), "=r"(v.y), "=r"(v.z), "=r"(v.w) : "r"(a)); return v; }
__device__ __forceinline__ float4 lds128f(uint32_t a) { float4 v; asm volatile("ld.shared.v4.f32 {%0,%1,%2,%3}, [%4];" : "=f"(v.x), "=f"(v.y), "=f"(v.z), "=f"(v.w) : "r"(a)); return v; }
__device__ __forceinline__ void sts32(uint32_t a, uint32_t v) { asm volatile("st.shared.b32 [%0], %1;" :: "r"(a), "r"(v) : "memory"); }
__device__ __forceinline__ void sts128f(uint32_t a, float x, float y, float z, float w) { asm volatile("st.shared.v4.f32 [%0], {%1,%2,%3,%4};" :: "r"(a), "f"(x), "f"(y), "f"(z), "f"(w) : "memory"); }
__device__ __forceinline__ void ldsm4t(uint32_t a, uint32_t& r0, uint32_t& r1, uint32_t& r2, uint32_t& r3) {
  asm volatile("ldmatrix.sync.aligned.m8n8.x4.trans.shared.b16 {%0,%1,%2,%3}, [%4];" : "=r"(r0), "=r"(r1), "=r"(r2), "=r"(r3) : "r"(a));
}
__device__ __forceinline__ void stsm4(uint32_t a, uint32_t r0, uint32_t r1, uint32_t r2, uint32_t r3) {
  asm volatile("stmatrix.sync.aligned.m8n8.x4.shared.b16 [%0], {%1,%2,%3,%4};" :: "r"(a), "r"(r0), "r"(r1), "r"(r2), "r"(r3) : "memory");
}
__device__ __forceinline__ uint32_t bmul(uint32_t a, uint32_t b) { uint32_t d; asm("mul.rn.bf16x2 %0, %1, %2;" : "=r"(d) : "r"(a), "r"(b)); return d; }
__device__ __forceinline__ uint32_t badd(uint32_t a, uint32_t b) { uint32_t d; asm("add.rn.bf16x2 %0, %1, %2;" : "=r"(d) : "r"(a), "r"(b)); return d; }
__device__ __forceinline__ uint32_t bfma(uint32_t a, uint32_t b, uint32_t c) { uint32_t d; asm("fma.rn.bf16x2 %0, %1, %2, %3;" : "=r"(d) : "r"(a), "r"(b), "r"(c)); return d; }
__device__ __forceinline__ float blo(uint32_t v) { return __uint_as_float(v << 16); }
__device__ __forceinline__ float bhi(uint32_t v) { return __uint_as_float(v & 0xffff0000u); }
__device__ __forceinline__ uint32_t pack2(float lo, float hi) { uint32_t d; asm("cvt.rn.bf16x2.f32 %0, %1, %2;" : "=r"(d) : "f"(hi), "f"(lo)); return d; }
__device__ __forceinline__ uint64_t mkdesc(uint32_t addr, uint32_t lbo, uint32_t sbo, int swz) {
  return (uint64_t)((addr & 0x3FFFF) >> 4) | ((uint64_t)(lbo >> 4) << 16) | ((uint64_t)(sbo >> 4) << 32) | ((uint64_t)swz << 62);
}
__device__ __forceinline__ void wg_fence() { asm volatile("wgmma.fence.sync.aligned;" ::: "memory"); }
__device__ __forceinline__ void wg_commit() { asm volatile("wgmma.commit_group.sync.aligned;" ::: "memory"); }
template <int N> __device__ __forceinline__ void wg_wait() { asm volatile("wgmma.wait_group.sync.aligned %0;" :: "n"(N) : "memory"); }
template <int I0, int I1, int N> __device__ __forceinline__ void reg_fence(float (&d)[N]) {
#pragma unroll
  for (int i = I0; i < I1; i++) asm volatile("" : "+f"(d[i]) :: "memory");
}
template <int I0, int I1, int N> __device__ __forceinline__ void reg_rename(float (&d)[N]) {
#pragma unroll
  for (int i = I0; i < I1; i++) { float t; asm volatile("mov.b32 %0, %1;" : "=f"(t) : "f"(d[i]) : "memory"); d[i] = t; }
}
__device__ __forceinline__ uint64_t fresh(uint64_t d, uint64_t z) { asm volatile("add.u64 %0, %0, %1;" : "+l"(d) : "l"(z)); return d; }
template <int TA, int TB, int SZ>
__device__ __forceinline__ void wgmma_n64(float (&d)[SZ], uint64_t a, uint64_t ao, uint64_t b, uint64_t bo, int sd) {
  asm volatile("{ .reg .pred p; .reg .b64 da, db; setp.ne.b32 p, %36, 0; add.u64 da, %32, %33; add.u64 db, %34, %35;\n"
    "wgmma.mma_async.sync.aligned.m64n64k16.f32.bf16.bf16 {%0, %1, %2, %3, %4, %5, %6, %7, %8, %9, %10, %11, %12, %13, %14, %15, %16, %17, %18, %19, %20, %21, %22, %23, %24, %25, %26, %27, %28, %29, %30, %31}, da, db, p, 1, 1, %37, %38; }"
    : "+f"(d[0]), "+f"(d[1]), "+f"(d[2]), "+f"(d[3]), "+f"(d[4]), "+f"(d[5]), "+f"(d[6]), "+f"(d[7]), "+f"(d[8]), "+f"(d[9]), "+f"(d[10]), "+f"(d[11]), "+f"(d[12]), "+f"(d[13]), "+f"(d[14]), "+f"(d[15]), "+f"(d[16]), "+f"(d[17]), "+f"(d[18]), "+f"(d[19]), "+f"(d[20]), "+f"(d[21]), "+f"(d[22]), "+f"(d[23]), "+f"(d[24]), "+f"(d[25]), "+f"(d[26]), "+f"(d[27]), "+f"(d[28]), "+f"(d[29]), "+f"(d[30]), "+f"(d[31])
    : "l"(a), "l"(ao), "l"(b), "l"(bo), "r"(sd), "n"(TA), "n"(TB));
}
template <int TA, int TB, int SZ>
__device__ __forceinline__ void wgmma_n96(float (&d)[SZ], uint64_t a, uint64_t ao, uint64_t b, uint64_t bo, int sd) {
  asm volatile("{ .reg .pred p; .reg .b64 da, db; setp.ne.b32 p, %52, 0; add.u64 da, %48, %49; add.u64 db, %50, %51;\n"
    "wgmma.mma_async.sync.aligned.m64n96k16.f32.bf16.bf16 {%0, %1, %2, %3, %4, %5, %6, %7, %8, %9, %10, %11, %12, %13, %14, %15, %16, %17, %18, %19, %20, %21, %22, %23, %24, %25, %26, %27, %28, %29, %30, %31, %32, %33, %34, %35, %36, %37, %38, %39, %40, %41, %42, %43, %44, %45, %46, %47}, da, db, p, 1, 1, %53, %54; }"
    : "+f"(d[0]), "+f"(d[1]), "+f"(d[2]), "+f"(d[3]), "+f"(d[4]), "+f"(d[5]), "+f"(d[6]), "+f"(d[7]), "+f"(d[8]), "+f"(d[9]), "+f"(d[10]), "+f"(d[11]), "+f"(d[12]), "+f"(d[13]), "+f"(d[14]), "+f"(d[15]), "+f"(d[16]), "+f"(d[17]), "+f"(d[18]), "+f"(d[19]), "+f"(d[20]), "+f"(d[21]), "+f"(d[22]), "+f"(d[23]), "+f"(d[24]), "+f"(d[25]), "+f"(d[26]), "+f"(d[27]), "+f"(d[28]), "+f"(d[29]), "+f"(d[30]), "+f"(d[31]), "+f"(d[32]), "+f"(d[33]), "+f"(d[34]), "+f"(d[35]), "+f"(d[36]), "+f"(d[37]), "+f"(d[38]), "+f"(d[39]), "+f"(d[40]), "+f"(d[41]), "+f"(d[42]), "+f"(d[43]), "+f"(d[44]), "+f"(d[45]), "+f"(d[46]), "+f"(d[47])
    : "l"(a), "l"(ao), "l"(b), "l"(bo), "r"(sd), "n"(TA), "n"(TB));
}
template <int TA, int TB, int SZ>
__device__ __forceinline__ void wgmma_n128(float (&d)[SZ], uint64_t a, uint64_t ao, uint64_t b, uint64_t bo, int sd) {
  asm volatile("{ .reg .pred p; .reg .b64 da, db; setp.ne.b32 p, %68, 0; add.u64 da, %64, %65; add.u64 db, %66, %67;\n"
    "wgmma.mma_async.sync.aligned.m64n128k16.f32.bf16.bf16 {%0, %1, %2, %3, %4, %5, %6, %7, %8, %9, %10, %11, %12, %13, %14, %15, %16, %17, %18, %19, %20, %21, %22, %23, %24, %25, %26, %27, %28, %29, %30, %31, %32, %33, %34, %35, %36, %37, %38, %39, %40, %41, %42, %43, %44, %45, %46, %47, %48, %49, %50, %51, %52, %53, %54, %55, %56, %57, %58, %59, %60, %61, %62, %63}, da, db, p, 1, 1, %69, %70; }"
    : "+f"(d[0]), "+f"(d[1]), "+f"(d[2]), "+f"(d[3]), "+f"(d[4]), "+f"(d[5]), "+f"(d[6]), "+f"(d[7]), "+f"(d[8]), "+f"(d[9]), "+f"(d[10]), "+f"(d[11]), "+f"(d[12]), "+f"(d[13]), "+f"(d[14]), "+f"(d[15]), "+f"(d[16]), "+f"(d[17]), "+f"(d[18]), "+f"(d[19]), "+f"(d[20]), "+f"(d[21]), "+f"(d[22]), "+f"(d[23]), "+f"(d[24]), "+f"(d[25]), "+f"(d[26]), "+f"(d[27]), "+f"(d[28]), "+f"(d[29]), "+f"(d[30]), "+f"(d[31]), "+f"(d[32]), "+f"(d[33]), "+f"(d[34]), "+f"(d[35]), "+f"(d[36]), "+f"(d[37]), "+f"(d[38]), "+f"(d[39]), "+f"(d[40]), "+f"(d[41]), "+f"(d[42]), "+f"(d[43]), "+f"(d[44]), "+f"(d[45]), "+f"(d[46]), "+f"(d[47]), "+f"(d[48]), "+f"(d[49]), "+f"(d[50]), "+f"(d[51]), "+f"(d[52]), "+f"(d[53]), "+f"(d[54]), "+f"(d[55]), "+f"(d[56]), "+f"(d[57]), "+f"(d[58]), "+f"(d[59]), "+f"(d[60]), "+f"(d[61]), "+f"(d[62]), "+f"(d[63])
    : "l"(a), "l"(ao), "l"(b), "l"(bo), "r"(sd), "n"(TA), "n"(TB));
}
__device__ __forceinline__ void wgmma_rs_n32(float (&d)[64], const uint32_t* a, uint64_t b, uint64_t bo, int sd) {
  asm volatile("{ .reg .pred p; .reg .b64 db; setp.ne.b32 p, %22, 0; add.u64 db, %20, %21;\n"
    "wgmma.mma_async.sync.aligned.m64n32k16.f32.bf16.bf16 {%0, %1, %2, %3, %4, %5, %6, %7, %8, %9, %10, %11, %12, %13, %14, %15}, {%16, %17, %18, %19}, db, p, 1, 1, 0; }"
    : "+f"(d[48]), "+f"(d[49]), "+f"(d[50]), "+f"(d[51]), "+f"(d[52]), "+f"(d[53]), "+f"(d[54]), "+f"(d[55]), "+f"(d[56]), "+f"(d[57]), "+f"(d[58]), "+f"(d[59]), "+f"(d[60]), "+f"(d[61]), "+f"(d[62]), "+f"(d[63])
    : "r"(a[0]), "r"(a[1]), "r"(a[2]), "r"(a[3]), "l"(b), "l"(bo), "r"(sd));
}
__device__ __forceinline__ void wgmma_rs_n64(float (&d)[64], const uint32_t* a, uint64_t b, uint64_t bo, int sd) {
  asm volatile("{ .reg .pred p; .reg .b64 db; setp.ne.b32 p, %38, 0; add.u64 db, %36, %37;\n"
    "wgmma.mma_async.sync.aligned.m64n64k16.f32.bf16.bf16 {%0, %1, %2, %3, %4, %5, %6, %7, %8, %9, %10, %11, %12, %13, %14, %15, %16, %17, %18, %19, %20, %21, %22, %23, %24, %25, %26, %27, %28, %29, %30, %31}, {%32, %33, %34, %35}, db, p, 1, 1, 0; }"
    : "+f"(d[32]), "+f"(d[33]), "+f"(d[34]), "+f"(d[35]), "+f"(d[36]), "+f"(d[37]), "+f"(d[38]), "+f"(d[39]), "+f"(d[40]), "+f"(d[41]), "+f"(d[42]), "+f"(d[43]), "+f"(d[44]), "+f"(d[45]), "+f"(d[46]), "+f"(d[47]), "+f"(d[48]), "+f"(d[49]), "+f"(d[50]), "+f"(d[51]), "+f"(d[52]), "+f"(d[53]), "+f"(d[54]), "+f"(d[55]), "+f"(d[56]), "+f"(d[57]), "+f"(d[58]), "+f"(d[59]), "+f"(d[60]), "+f"(d[61]), "+f"(d[62]), "+f"(d[63])
    : "r"(a[0]), "r"(a[1]), "r"(a[2]), "r"(a[3]), "l"(b), "l"(bo), "r"(sd));
}
__device__ __forceinline__ void wgmma_rs_n96(float (&d)[64], const uint32_t* a, uint64_t b, uint64_t bo, int sd) {
  asm volatile("{ .reg .pred p; .reg .b64 db; setp.ne.b32 p, %54, 0; add.u64 db, %52, %53;\n"
    "wgmma.mma_async.sync.aligned.m64n96k16.f32.bf16.bf16 {%0, %1, %2, %3, %4, %5, %6, %7, %8, %9, %10, %11, %12, %13, %14, %15, %16, %17, %18, %19, %20, %21, %22, %23, %24, %25, %26, %27, %28, %29, %30, %31, %32, %33, %34, %35, %36, %37, %38, %39, %40, %41, %42, %43, %44, %45, %46, %47}, {%48, %49, %50, %51}, db, p, 1, 1, 0; }"
    : "+f"(d[16]), "+f"(d[17]), "+f"(d[18]), "+f"(d[19]), "+f"(d[20]), "+f"(d[21]), "+f"(d[22]), "+f"(d[23]), "+f"(d[24]), "+f"(d[25]), "+f"(d[26]), "+f"(d[27]), "+f"(d[28]), "+f"(d[29]), "+f"(d[30]), "+f"(d[31]), "+f"(d[32]), "+f"(d[33]), "+f"(d[34]), "+f"(d[35]), "+f"(d[36]), "+f"(d[37]), "+f"(d[38]), "+f"(d[39]), "+f"(d[40]), "+f"(d[41]), "+f"(d[42]), "+f"(d[43]), "+f"(d[44]), "+f"(d[45]), "+f"(d[46]), "+f"(d[47]), "+f"(d[48]), "+f"(d[49]), "+f"(d[50]), "+f"(d[51]), "+f"(d[52]), "+f"(d[53]), "+f"(d[54]), "+f"(d[55]), "+f"(d[56]), "+f"(d[57]), "+f"(d[58]), "+f"(d[59]), "+f"(d[60]), "+f"(d[61]), "+f"(d[62]), "+f"(d[63])
    : "r"(a[0]), "r"(a[1]), "r"(a[2]), "r"(a[3]), "l"(b), "l"(bo), "r"(sd));
}
__device__ __forceinline__ void wgmma_rs_n128(float (&d)[64], const uint32_t* a, uint64_t b, uint64_t bo, int sd) {
  asm volatile("{ .reg .pred p; .reg .b64 db; setp.ne.b32 p, %70, 0; add.u64 db, %68, %69;\n"
    "wgmma.mma_async.sync.aligned.m64n128k16.f32.bf16.bf16 {%0, %1, %2, %3, %4, %5, %6, %7, %8, %9, %10, %11, %12, %13, %14, %15, %16, %17, %18, %19, %20, %21, %22, %23, %24, %25, %26, %27, %28, %29, %30, %31, %32, %33, %34, %35, %36, %37, %38, %39, %40, %41, %42, %43, %44, %45, %46, %47, %48, %49, %50, %51, %52, %53, %54, %55, %56, %57, %58, %59, %60, %61, %62, %63}, {%64, %65, %66, %67}, db, p, 1, 1, 0; }"
    : "+f"(d[0]), "+f"(d[1]), "+f"(d[2]), "+f"(d[3]), "+f"(d[4]), "+f"(d[5]), "+f"(d[6]), "+f"(d[7]), "+f"(d[8]), "+f"(d[9]), "+f"(d[10]), "+f"(d[11]), "+f"(d[12]), "+f"(d[13]), "+f"(d[14]), "+f"(d[15]), "+f"(d[16]), "+f"(d[17]), "+f"(d[18]), "+f"(d[19]), "+f"(d[20]), "+f"(d[21]), "+f"(d[22]), "+f"(d[23]), "+f"(d[24]), "+f"(d[25]), "+f"(d[26]), "+f"(d[27]), "+f"(d[28]), "+f"(d[29]), "+f"(d[30]), "+f"(d[31]), "+f"(d[32]), "+f"(d[33]), "+f"(d[34]), "+f"(d[35]), "+f"(d[36]), "+f"(d[37]), "+f"(d[38]), "+f"(d[39]), "+f"(d[40]), "+f"(d[41]), "+f"(d[42]), "+f"(d[43]), "+f"(d[44]), "+f"(d[45]), "+f"(d[46]), "+f"(d[47]), "+f"(d[48]), "+f"(d[49]), "+f"(d[50]), "+f"(d[51]), "+f"(d[52]), "+f"(d[53]), "+f"(d[54]), "+f"(d[55]), "+f"(d[56]), "+f"(d[57]), "+f"(d[58]), "+f"(d[59]), "+f"(d[60]), "+f"(d[61]), "+f"(d[62]), "+f"(d[63])
    : "r"(a[0]), "r"(a[1]), "r"(a[2]), "r"(a[3]), "l"(b), "l"(bo), "r"(sd));
}

__device__ __forceinline__ void st_either(bool loc, uint32_t a, uint32_t x, uint32_t y, uint32_t z, uint32_t w, uint32_t bar) {
  if (loc) asm volatile("st.shared.v4.b32 [%0], {%1,%2,%3,%4};" :: "r"(a), "r"(x), "r"(y), "r"(z), "r"(w) : "memory");
  else st_async4(a, x, y, z, w, bar);
}
__device__ __forceinline__ void prep_task(bool loc, uint32_t src, uint32_t dst, uint32_t bar, uint32_t w0, uint32_t w1, uint32_t w2, uint32_t w3) {
  uint32_t k[12], u[9];
#pragma unroll
  for (int j = 0; j < 12; j++) k[j] = lds32(j < 4 ? src + (4 + j) * 528 - 16 : src + (j - 4) * 528);
#pragma unroll
  for (int j = 0; j < 9; j++) u[j] = lds32(j < 1 ? src + 4224 + 7 * 528 - 16 : src + 4224 + (j - 1) * 528);
#pragma unroll
  for (int j = 0; j < 9; j++) {
    uint32_t s = bmul(k[j], w3);
    s = bfma(k[j + 1], w2, s); s = bfma(k[j + 2], w1, s); s = bfma(k[j + 3], w0, s);
    u[j] = bmul(s, u[j]);
  }
#pragma unroll
  for (int c = 0; c < 2; c++) {
    const uint32_t sel = c ? 0x7632 : 0x5410;
    st_either(loc, dst + c * U_PITCH, __byte_perm(u[2], u[1], sel), __byte_perm(u[4], u[3], sel), __byte_perm(u[6], u[5], sel), __byte_perm(u[8], u[7], sel), bar);
    st_either(loc, dst + c * U_PITCH + U_ODD, __byte_perm(u[1], u[0], sel), __byte_perm(u[3], u[2], sel), __byte_perm(u[5], u[4], sel), __byte_perm(u[7], u[6], sel), bar);
  }
}

template <int S, int C0, int NK>
__device__ __forceinline__ void frag_load(uint32_t (&P)[4 * NK], uint32_t ua, uint32_t z) {
  P[2] = lds32(ua + 1024 * S + 32 * C0 - 16);
#pragma unroll
  for (int kk = 0; kk < NK; kk++) { P[4 * kk] = lds32(ua + 1024 * S + 32 * (C0 + kk)); P[4 * kk + 1] = lds32(ua + 1024 * S + 32 * (C0 + kk) + 16); }
#pragma unroll
  for (int kk = 0; kk < NK; kk++) { P[4 * kk + 3] = P[4 * kk] ^ z; if (kk) P[4 * kk + 2] = P[4 * kk - 3] ^ z; }
#pragma unroll
  for (int i = 0; i < 4 * NK; i++) asm volatile("" : "+r"(P[i]) :: "memory");
}
template <int S, int C0, int NK, int CH>
__device__ __forceinline__ void conv_issue(float (&acc)[64], const uint32_t (&P)[4 * NK], uint64_t& db, uint64_t z64) {
  if (S > 0 && C0 == 0) reg_rename<16 * S, 64>(acc);
  if (C0 == 0 && CH == 0) db = fresh(db, z64);
  wg_fence();
#pragma unroll
  for (int kk = 0; kk < NK; kk++) {
    const uint64_t o = 16 - 2 * (C0 + kk) + CH * (T_PITCH / 8);
    if (S == 0) wgmma_rs_n128(acc, &P[4 * kk], db, o, C0 + kk != 0);
    if (S == 1) wgmma_rs_n96(acc, &P[4 * kk], db, o, 1);
    if (S == 2) wgmma_rs_n64(acc, &P[4 * kk], db, o, 1);
    if (S == 3) wgmma_rs_n32(acc, &P[4 * kk], db, o, 1);
  }
  wg_commit();
}
template <int S>
__device__ __forceinline__ void conv_dump(float (&acc)[64], uint32_t xw, int wl) {
  reg_fence<16 * S, 16 * S + 16>(acc);
#pragma unroll
  for (int r = 0; r < 3; r++) {
    const int i = 16 * S + 4 * (r + 1);
    if (S < 3 || wl + r + 1 < 4) sts64(xw + (4 * S + r + 1) * 768 + r * 256, pack2(acc[i], acc[i + 1]), pack2(acc[i + 2], acc[i + 3]));
  }
}
template <int S>
__device__ __forceinline__ void conv_reduce(float (&y)[4], const float (&acc)[64], uint32_t xw, int wl) {
#pragma unroll
  for (int i = 0; i < 4; i++) y[i] = acc[16 * S + i];
  uint2 v[3];
#pragma unroll
  for (int r = 0; r < 3; r++) {
    v[r] = make_uint2(0u, 0u);
    if (S > 0 || r < wl) v[r] = lds64(xw + 4 * S * 768 + r * 256);
  }
#pragma unroll
  for (int r = 0; r < 3; r++) {
    if (r < RED_H2) { v[r + 1].x = badd(v[r].x, v[r + 1].x); v[r + 1].y = badd(v[r].y, v[r + 1].y); }
    else { y[0] += blo(v[r].x); y[1] += bhi(v[r].x); y[2] += blo(v[r].y); y[3] += bhi(v[r].y); }
  }
}
struct FinCtx { uint32_t um, xt, st, DA, DB; uint32_t *hA, *hB; };
template <int S>
__device__ __forceinline__ void conv_z(uint32_t (&zz)[4], const FinCtx& c, const float (&aA)[64], const float (&aB)[64], uint32_t xA, uint32_t xB, int wl) {
  uint32_t u[4];
  float ya[4], yb[4];
  ldsm4t(c.um + S * 1024, u[0], u[1], u[2], u[3]);
  conv_reduce<S>(ya, aA, xA, wl); conv_reduce<S>(yb, aB, xB, wl);
  zz[0] = bfma(u[0], c.DA, pack2(ya[0], ya[1])); zz[1] = bfma(u[1], c.DA, pack2(ya[2], ya[3]));
  zz[2] = bfma(u[2], c.DB, pack2(yb[0], yb[1])); zz[3] = bfma(u[3], c.DB, pack2(yb[2], yb[3]));
}
template <int S>
__device__ __forceinline__ void conv_fin(const FinCtx& c, const uint32_t (&zz)[4]) {
  constexpr uint32_t XO = (S < 2 ? OFF_XTE : OFF_XTL) + (S & 1) * 4096, SO = (S < 2 ? OFF_STE : OFF_STL) + (S & 1) * 2048;
#pragma unroll
  for (int h = 0; h < 2; h++) {
    uint2 sv = lds64(c.st + SO + h * 256);
    uint32_t xa = lds32(c.xt + XO + h * 512), xb = lds32((c.xt ^ 64) + XO + h * 512);
    c.hA[(8 * S + h) * (D_ * 32)] = bfma(bfma(xa, sv.x, sv.y), zz[h], xa);
    c.hB[(8 * S + h) * (D_ * 32)] = bfma(bfma(xb, sv.x, sv.y), zz[2 + h], xb);
  }
}

struct RowC { float nm, k1, k2, hs; };
__device__ __forceinline__ float geglu(float g, float u, float cg, float cu, const RowC& r) {
  if (WHATIF & 1) return g * u;
  float gc = fmaf(r.nm, cg, g), uc = fmaf(r.nm, cu, u);
  if (WHATIF & (32 | 128)) { gc = g; uc = u; }
  if (WHATIF & 256) { gc = fmaf(r.nm, r.k1, g); uc = fmaf(r.nm, r.k2, u); }
  if (WHATIF & 512) { gc = g + r.nm; uc = u + r.nm; }
  float in = gc * fmaf(gc * gc, r.k2, r.k1);
  float t; asm("tanh.approx.f32 %0, %1;" : "=f"(t) : "f"(in));
  float pr = gc * uc;
  return fmaf(pr, t, pr);
}
template <int GI, int UI, int N>
__device__ __forceinline__ void epi_group(const float (&acc)[N], const float4& c, const RowC& r0, const RowC& r1, uint32_t* dst) {
  uint32_t lo = pack2(geglu(acc[GI], acc[UI], c.x, c.z, r0), geglu(acc[GI + 1], acc[UI + 1], c.y, c.w, r0));
  uint32_t hi = pack2(geglu(acc[GI + 2], acc[UI + 2], c.x, c.z, r1), geglu(acc[GI + 3], acc[UI + 3], c.y, c.w, r1));
  if (WHATIF & 128) { lo ^= (__float_as_uint(c.x) & __float_as_uint(c.y)) >> 31; hi ^= (__float_as_uint(c.z) & __float_as_uint(c.w)) >> 31; }
  dst[0] = lo; dst[32] = hi;
}

struct Params {
  const uint16_t *x, *shift_k, *ssm_k, *ssm_D, *wg, *wu, *wd;
  uint16_t* out;
  Scratch* scr;
  uint64_t z64;
};

__global__ void __launch_bounds__(NTHR, 1)
fused_kernel(const Params p, const __grid_constant__ CUtensorMap tmXR, const __grid_constant__ CUtensorMap tmT, const __grid_constant__ CUtensorMap tmK, const __grid_constant__ CUtensorMap tmV,
             const __grid_constant__ CUtensorMap tmG, const __grid_constant__ CUtensorMap tmU,
             const __grid_constant__ CUtensorMap tmG32, const __grid_constant__ CUtensorMap tmU32,
             const __grid_constant__ CUtensorMap tmD, const __grid_constant__ CUtensorMap tmX, const __grid_constant__ CUtensorMap tmO) {
  extern __shared__ __align__(1024) uint8_t smem[];
  const uint32_t sb = s2u(smem);
  const int xb = blockIdx.x;
  auto x_load = [&]() {
    const uint32_t b = sb + OFF_BAR + B_XR * 8;
    mbar_init(b, 1);
    mbar_expect(b, 16384);
    asm volatile("cp.async.bulk.tensor.4d.shared::cluster.global.mbarrier::complete_tx::bytes [%0], [%1, {%3, %4, %5, %3}], [%2];"
                 :: "r"(sb + OFF_XR), "l"(&tmXR), "r"(b), "r"(0), "r"((xb & 7) * 2), "r"(xb & ~7) : "memory");
  };
  if (FRONT_ORD == 0 && (threadIdx.x >> 5) == X_WARP) { if (elect()) x_load(); __syncwarp(); }
  if (TM_PF && (threadIdx.x >> 5) == 2 && elect()) {
    asm volatile("prefetch.tensormap [%0];" :: "l"(&tmK) : "memory");
    asm volatile("prefetch.tensormap [%0];" :: "l"(&tmV) : "memory");
    asm volatile("prefetch.tensormap [%0];" :: "l"(&tmT) : "memory");
  }
  const int rank = blockIdx.x & 1, cl = blockIdx.x >> 1;
  const int q7 = ((cl - 36) * 37) >> 8, p8 = 4 + ((cl - 4) & 7) * 4 + ((cl - 4) >> 3), p7 = 4 * cl - 108 - 27 * q7;
  const int pair = cl < 4 ? cl : cl < 36 ? p8 : p7;
  const int bid = pair * 2 + rank;
  const int tile = bid >> 3, js = bid & 7;
  auto BAR = [&](int i) { return sb + OFF_BAR + i * 8; };
  auto kv_load = [&](int pc) {
    uint32_t b = BAR(B_KV + pc), d = sb + OFF_KV + pc * KV_PIECE;
    int run0 = pc * 64 + rank * 32 - 1;
    mbar_expect(b, KV_PIECE);
    tma3d(d, &tmK, pair * 8, run0, 0, b);
    tma3d(d + 4224, &tmV, pair * 8, run0, 0, b);
  };
  if (threadIdx.x < 32) {
    if (elect()) {
      mbar_init(BAR(B_KV), 1);
      kv_load(0);
      if (FRONT_ORD == 1) x_load();
#pragma unroll
      for (int i = 0; i < 2; i++) {
        mbar_init(BAR(B_TAP + i), 1);
        mbar_expect(BAR(B_TAP + i), 2 * T_PITCH);
        tma3d(sb + OFF_TAP + i * 2 * T_PITCH, &tmT, 0, -1, bid * 4 + 2 * i, BAR(B_TAP + i));
        if (FRONT_ORD == 2 + i) x_load();
      }
#pragma unroll
      for (int i = 0; i < 3; i++) { mbar_init(BAR(B_KV + 1 + i), 1); mbar_init(BAR(B_CS + i), 1); }
      SSTAMP(true, 26);
    }
    __syncwarp();
  }
  const int tid = (threadIdx.x + 384) & 511, lane = tid & 31;
  const int warp = __shfl_sync(0xffffffffu, tid >> 5, 0);
  const int g = lane >> 2, q = lane & 3;
  uint4 small;
  if (warp >= 8) {
    if (warp != 12 && elect()) {
      const int cnt = warp < 10 ? 8 : (warp < 12 ? 4 : 1), cnt0 = warp == 13 ? 5 : cnt;
#pragma unroll
      for (int i = 0; i < 10; i++) mbar_init(BAR((warp - 8) * 10 + i), i < 4 ? cnt0 : (warp == 9 || (i == 9 && warp == 11) ? 1 : cnt));
      asm volatile("fence.mbarrier_init.release.cluster;" ::: "memory");
      if (warp == 13) {
#pragma unroll
        for (int i = 0; i < 8; i++) mbar_expect(BAR(B_U + i), i < 4 ? 4096 : i < 6 ? 8192 : 512);
      }
    }
    __syncwarp();
    if (warp < 12) small = __ldg((const uint4*)(p.shift_k + (pair * 8 + 2 * q) * 4));
    else small.x = p.scr->epoch[bid];
  } else {
    const uint2 d4 = __ldg((const uint2*)(p.ssm_D + bid * 4));
    small.x = d4.x; small.y = d4.y;
    if (tid < 64) sts32(sb + OFF_U + (tid >> 4) * U_PITCH + ((tid >> 3) & 1) * U_ODD + (tid & 7) * 4, 0u);
  }
  __syncthreads();
  asm volatile("barrier.cluster.arrive.relaxed.aligned;" ::: "memory");
  SSTAMP(tid == 0, 13);

  if (warp < 8) {
    asm volatile("setmaxnreg.inc.sync.aligned.u32 %0;" :: "n"(REG_C));
    {
      mbar_wait(BAR(B_XR), 0);
      SSTAMP(tid == 0, 49);
      const int mi = lane >> 3, rho = lane & 7;
      const int t = (rho & 1) + 4 * (rho >> 1) + 2 * (mi & 1);
      const int xrow = 2 * (t & 7) + ((t >> 3) ^ 1);
      const uint32_t xa = sb + OFF_XR + warp * 2048 + xrow * 128 + (((mi >> 1) ^ (xrow & 7)) * 16);
      const uint32_t xo = sb + OFF_XST + warp * 2048 + (g ^ (xb & 3)) * 32 + q * 8;
#pragma unroll
      for (int i = 0; i < 4; i++) {
        uint32_t m0, m1, m2, m3;
        ldsm4t(xa ^ (i * 32), m0, m1, m2, m3);
        sts64(xo + i * 512, m0, m1);
        sts64(xo + i * 512 + 256, m2, m3);
      }
      if (X_SPLIT) { __syncwarp(); if (lane == 0) mbar_arrive(BAR(B_SIGT)); }
      const int r = tid >> 4;
      const uint32_t ra = sb + OFF_XR + (2 * (r & 7) + ((r >> 3) ^ 1)) * 128 + (mi & 1) * 2048 + rho * 16;
      float f[32];
#pragma unroll
      for (int i = 0; i < 4; i++) {
        uint4 v = lds128(ra + i * 4096);
        f[8 * i] = blo(v.x); f[8 * i + 1] = bhi(v.x); f[8 * i + 2] = blo(v.y); f[8 * i + 3] = bhi(v.y);
        f[8 * i + 4] = blo(v.z); f[8 * i + 5] = bhi(v.z); f[8 * i + 6] = blo(v.w); f[8 * i + 7] = bhi(v.w);
      }
      float sa = 0.f, sc = 0.f;
#pragma unroll
      for (int i = 0; i < 16; i++) { sa += f[2 * i]; sc += f[2 * i + 1]; }
      sa += sc;
#pragma unroll
      for (int o = 1; o < 16; o <<= 1) sa += __shfl_xor_sync(0xffffffffu, sa, o);
      const float mean = sa * (1.f / D_);
      float qa = 0.f, qc = 0.f;
#pragma unroll
      for (int i = 0; i < 16; i++) { float d0 = f[2 * i] - mean, d1 = f[2 * i + 1] - mean; qa = fmaf(d0, d0, qa); qc = fmaf(d1, d1, qc); }
      qa += qc;
#pragma unroll
      for (int o = 1; o < 16; o <<= 1) qa += __shfl_xor_sync(0xffffffffu, qa, o);
      const float rs = blo(pack2(rsqrtf(fmaf(qa, 1.f / D_, 1e-5f)), 0.f));
      const uint32_t me = pack2(rs, -mean * rs), ot = __shfl_xor_sync(0xffffffffu, me, 16);
      if (lane == 0) sts64(sb + OFF_CS + warp * 8, __byte_perm(me, ot, 0x5410), __byte_perm(me, ot, 0x7632));
      __syncwarp();
      if (lane == 0) mbar_arrive(BAR(B_SIGX));
      { float w0;
        asm volatile("{ .reg .f32 a, b, c; mma.sync.aligned.m16n8k8.row.col.f32.bf16.bf16.f32 {%0,a,b,c}, {%1,%1}, {%1}, {%2,%2,%2,%2}; }"
                     : "=f"(w0) : "r"(blockIdx.x >> 16), "f"(0.f));
        small.x ^= __float_as_uint(w0); }
      SSTAMP(tid == 0, 48);
    }
    const int hw = warp >> 2, wl = warp & 3;
    {
      const int chA = bid * 4 + hw, chB = chA + 2;
      const int ig = g ^ 1;
      const uint32_t uA = sb + OFF_U + hw * U_PITCH + ((ig & 1) ? 0 : U_ODD) + 32 + ((ig - 2 * q) >> 1) * 4 + wl * 256;
      const uint32_t uB = uA + 2 * U_PITCH;
      uint64_t dT = mkdesc(sb + OFF_TAP + hw * T_PITCH, 16, 256, 3);
      const uint32_t z = blockIdx.x >> 16;
      const uint32_t xA = sb + OFF_XCH + (hw * 32 + wl) * 768 + lane * 8, xB = xA + 16 * 768;
      FinCtx fc;
      fc.um = sb + OFF_U + (hw + 2 * (lane >> 4)) * U_PITCH + 32 + wl * 256 + (lane & 7) * 32 + ((lane >> 3) & 1) * 16;
      fc.xt = sb + wl * 1024 + (lane >> 3) * 128 + (hw ^ (lane >> 3)) * 32 + (lane & 7) * 4;
      fc.st = sb + wl * 512 + lane * 8;
      fc.DA = __byte_perm(small.x, 0, hw ? 0x3232 : 0x1010); fc.DB = __byte_perm(small.y, 0, hw ? 0x3232 : 0x1010);
      fc.hA = (uint32_t*)p.scr->hT + (size_t)wl * 2 * (D_ * 32) + chA * 32 + ((g ^ (chA & 7)) * 4) + q;
      fc.hB = (uint32_t*)p.scr->hT + (size_t)wl * 2 * (D_ * 32) + chB * 32 + ((g ^ (chB & 7)) * 4) + q;
      asm volatile("barrier.cluster.wait.aligned;" ::: "memory");
      auto tap_fix = [&](int i) {
        const uint32_t a = sb + OFF_TAP + (hw + 2 * i) * T_PITCH + 256 + ((tid & 127) >> 3) * 256 + 128 + (tid & 7) * 16;
        mbar_wait(BAR(B_TAP + i), 0);
        const uint4 v = lds128(a);
        __syncwarp();
        asm volatile("st.shared.v4.b32 [%0], {%1,%2,%3,%4};" :: "r"(a ^ 16), "r"(v.x), "r"(v.y), "r"(v.z), "r"(v.w) : "memory");
        fence_async_s();
        bar_sync(1 + hw, 128);
      };
      tap_fix(0);
      SSTAMP(tid == 0, 2);
      float aA[64], aB[64];
      uint32_t z0[4], z1[4];
      {
        uint32_t P[16], Q[16];
        mbar_wait_cluster(BAR(B_U + 0), 0);
        SSTAMP(tid == 0, 3);
        frag_load<0, 0, 4>(P, uA, z); conv_issue<0, 0, 4, 0>(aA, P, dT, p.z64);
        frag_load<0, 4, 4>(Q, uA, z); conv_issue<0, 4, 4, 0>(aA, Q, dT, p.z64);
        tap_fix(1);
        wg_wait<1>(); frag_load<0, 0, 4>(P, uB, z); conv_issue<0, 0, 4, 1>(aB, P, dT, p.z64);
        wg_wait<1>(); frag_load<0, 4, 4>(Q, uB, z); conv_issue<0, 4, 4, 1>(aB, Q, dT, p.z64);
        conv_dump<0>(aA, xA, wl);
        SSTAMP(tid == 0, 4);
        mbar_wait_cluster(BAR(B_U + 1), 0);
        SSTAMP(tid == 0, 5);
        wg_wait<1>(); frag_load<1, 0, 4>(P, uA, z); conv_issue<1, 0, 4, 0>(aA, P, dT, p.z64);
        wg_wait<1>(); frag_load<1, 4, 4>(Q, uA, z); conv_issue<1, 4, 4, 0>(aA, Q, dT, p.z64);
        conv_dump<0>(aB, xB, wl);
        wg_wait<1>(); frag_load<1, 0, 4>(P, uB, z); conv_issue<1, 0, 4, 1>(aB, P, dT, p.z64);
        bar_sync(1 + hw, 128);
        conv_z<0>(z0, fc, aA, aB, xA, xB, wl);
        wg_wait<1>(); frag_load<1, 4, 4>(Q, uB, z); conv_issue<1, 4, 4, 1>(aB, Q, dT, p.z64);
        conv_dump<1>(aA, xA, wl);
      }
      {
        uint32_t P[32], Q[32], R[32];
        SSTAMP(tid == 0, 6);
        mbar_wait_cluster(BAR(B_U + 2), 0);
        wg_wait<1>(); frag_load<2, 0, 8>(P, uA, z); conv_issue<2, 0, 8, 0>(aA, P, dT, p.z64);
        frag_load<2, 0, 8>(Q, uB, z); wg_wait<1>(); conv_issue<2, 0, 8, 1>(aB, Q, dT, p.z64);
        conv_dump<1>(aB, xB, wl);
        bar_sync(1 + hw, 128);
        conv_z<1>(z1, fc, aA, aB, xA, xB, wl);
        SSTAMP(tid == 0, 1);
        if (CONV_ORDER != 4) mbar_wait(BAR(B_XT), 0);
        SSTAMP(tid == 0, 7);
        if (CONV_ORDER != 4) conv_fin<0>(fc, z0);
        conv_fin<1>(fc, z1);
        __syncwarp();
        if (lane == 0) mbar_arrive(BAR(B_SIGE + 0));
        SSTAMP(tid == 0, 8);
        mbar_wait_cluster(BAR(B_U + 3), 0);
        frag_load<3, 0, 8>(R, uA, z); wg_wait<1>(); conv_issue<3, 0, 8, 0>(aA, R, dT, p.z64);
        frag_load<3, 0, 8>(P, uB, z); wg_wait<1>(); conv_issue<3, 0, 8, 1>(aB, P, dT, p.z64);
        SSTAMP(tid == 0, 9);
        conv_dump<2>(aA, xA, wl); conv_dump<2>(aB, xB, wl);
        wg_wait<0>();
        conv_dump<3>(aA, xA, wl); conv_dump<3>(aB, xB, wl);
        SSTAMP(tid == 0, 10);
        bar_sync(1 + hw, 128);
        mbar_wait(BAR(B_XT + 1), 0);
        SSTAMP(tid == 0, 11);
        conv_z<2>(z0, fc, aA, aB, xA, xB, wl);
        conv_fin<2>(fc, z0);
        conv_z<3>(z1, fc, aA, aB, xA, xB, wl);
        conv_fin<3>(fc, z1);
        __syncwarp();
        if (lane == 0) mbar_arrive(BAR(B_SIGE + 1));
        STAMP_IF(tid == 0, 12);
      }
    }
    const int blk = tile + 16 * hw;
    const uint32_t aw = sb + OFF_A + hw * 65536;
    const uint32_t fullA = BAR(B_FULLA + hw * 8), emptyA = BAR(B_EMPTYA + hw * 6);
    const uint32_t lmo = aw + (((lane >> 4) * 8 + (lane & 7)) * 128) + (((2 * wl + ((lane >> 3) & 1)) ^ (lane & 7)) * 16);
    uint64_t da = fresh(mkdesc(aw - 16, 0, 1024, 1), p.z64), db = fresh(mkdesc(sb + OFF_RING - 16, 8192, 1024, 1), p.z64);
    float acc1[64], acc2[64];
    RowC r0, r1;
    const int TS = 16 + hw * 16; (void)TS;

    const uint32_t csa = sb + OFF_CS + q * 16;
    float4 cc[22];
    auto ldcs = [&](int i0, int i1) {
#pragma unroll
      for (int i = i0; i < i1; i += 2) {
        const uint4 v = lds128(csa + i * 32);
        cc[i] = make_float4(blo(v.x), __uint_as_float(v.x), blo(v.y), __uint_as_float(v.y));
        cc[i + 1] = make_float4(blo(v.z), __uint_as_float(v.z), blo(v.w), __uint_as_float(v.w));
      }
    };
    uint32_t res[16];
    auto ldres = [&]() {
#pragma unroll
      for (int kk = 0; kk < 4; kk++) ldsm4t(lmo + js * 8192 + kk * 2048, res[4 * kk], res[4 * kk + 1], res[4 * kk + 2], res[4 * kk + 3]);
    };
#pragma unroll
    for (int s = 0; s < 8; s++) {
      mbar_wait(fullA + s * 8, 0);
      STAMP_IF(wl == 0 && lane == 0 && s == 0, TS + 0);
      mbar_wait(BAR(B_FULLR + s % 6), s >= 6);
      wg_fence();
#pragma unroll
      for (int kk = 0; kk < 4; kk++) wgmma_n128<1, 1>(acc1, da, 1 + s * 512 + kk * 128, db, 1 + (s % 6) * 1024 + kk * 128, (s | kk) != 0);
      wg_commit();
      if (s == 3) db = fresh(db, p.z64);
      if (CS_MODE == 2 && s == 7) { mbar_wait(BAR(B_CS), 0); ldcs(0, 4); }
      if (s > 0) { wg_wait<1>(); if (lane == 0) mbar_arrive(BAR(B_EMPTYR + (s - 1) % 6)); }
    }
    STAMP_IF(wl == 0 && lane == 0, TS + 1);
    uint32_t* hdst = (uint32_t*)p.scr->H + (size_t)blk * (86 * 512) + wl * 64 + lane;
    da = fresh(da, p.z64); db = fresh(db, p.z64);
#pragma unroll
    for (int s = 0; s < 8; s++) {
      constexpr int R0 = 8;
      const int r = R0 + s, slot = r % 6;
      mbar_wait(BAR(B_FULLR + slot), (r / 6) & 1);
      wg_fence();
#pragma unroll
      for (int kk = 0; kk < 4; kk++) wgmma_n128<1, 1>(acc2, da, 1 + s * 512 + kk * 128, db, 1 + slot * 1024 + kk * 128, (s | kk) != 0);
      if (s == 3) db = fresh(db, p.z64);
      wg_commit();
      uint32_t* d = hdst + js * 8 * 256;
      if (s == STX_AT) {
        mbar_wait_cluster(BAR(B_STX + hw), 0);
        auto mk = [](uint2 v) {
          const float rs = __uint_as_float(v.y), r2 = rs * rs;
          RowC r; r.nm = __uint_as_float(v.x); r.k1 = 0.7978845608028654f * rs; r.k2 = 0.044715f * r2 * r.k1; r.hs = 0.5f * r2;
          return r;
        };
        r0 = mk(lds64(sb + OFF_STX + warp * 128 + g * 8)); r1 = mk(lds64(sb + OFF_STX + warp * 128 + 64 + g * 8));
      }
      if (s == 0 && CS_MODE != 2) mbar_wait(BAR(B_CS), 0);
      if (s == 1) { reg_fence<0, 64>(acc1); epi_group<0, 32>(acc1, cc[0], r0, r1, d); epi_group<4, 36>(acc1, cc[1], r0, r1, d + 256); }
      if (s == 2) { epi_group<8, 40>(acc1, cc[2], r0, r1, d + 512); epi_group<12, 44>(acc1, cc[3], r0, r1, d + 768); }
      if (s == 3) { epi_group<16, 48>(acc1, cc[4], r0, r1, d + 1024); epi_group<20, 52>(acc1, cc[5], r0, r1, d + 1280); }
      if (s == 4) { epi_group<24, 56>(acc1, cc[6], r0, r1, d + 1536); epi_group<28, 60>(acc1, cc[7], r0, r1, d + 1792);
                    __syncwarp(); if (lane == 0) mbar_arrive(BAR(B_SIGH + 0)); }
      if (RES_EARLY && s == 5) ldres();
      if (CS_MODE == 0 && s <= 4) ldcs(2 * s, 2 * s + 2);
      if (CS_MODE == 1 && s <= 3) ldcs(2 * s, 2 * s + 2);
      if (CS_MODE == 2 && s == 0) ldcs(4, 8);
      if (CS_MODE == 3 && s == 0) ldcs(0, 8);
      if (CS_MODE > 0 && s >= 6) ldcs(8 + 4 * (s - 6), 12 + 4 * (s - 6));
      wg_wait<1>();
      if (lane == 0) mbar_arrive(BAR(B_EMPTYR + (r - 1) % 6));
    }
    STAMP_IF(wl == 0 && lane == 0, TS + 2);
    da = fresh(da, p.z64); db = fresh(mkdesc(sb + OFF_RING - 16, 4096, 512, 2), p.z64);
    float acc3[48];
#pragma unroll
    for (int s = 0; s < 8; s++) {
      constexpr int R0 = 16;
      const int r = R0 + s, slot = r % 6;
      mbar_wait(BAR(B_FULLR + slot), (r / 6) & 1);
      wg_fence();
#pragma unroll
      for (int kk = 0; kk < 4; kk++) wgmma_n96<1, 1>(acc3, da, 1 + s * 512 + kk * 128, db, 1 + slot * 1024 + kk * 64, (s | kk) != 0);
      if (s == 3) db = fresh(db, p.z64);
      wg_commit();
      uint32_t* d = hdst + (64 + js * 8) * 256;
      if (s == 0) {
        if (!RES_EARLY) ldres();
        wg_wait<1>();
        if (lane == 0) mbar_arrive(BAR(B_EMPTYR + (r - 1) % 6));
        reg_fence<0, 64>(acc2);
        epi_group<0, 32>(acc2, cc[8], r0, r1, d); epi_group<4, 36>(acc2, cc[9], r0, r1, d + 256);
      }
      if (s == 1) { epi_group<8, 40>(acc2, cc[10], r0, r1, d + 512); epi_group<12, 44>(acc2, cc[11], r0, r1, d + 768); }
      if (s == 2) { epi_group<16, 48>(acc2, cc[12], r0, r1, d + 1024); epi_group<20, 52>(acc2, cc[13], r0, r1, d + 1280); }
      if (s == 3) { epi_group<24, 56>(acc2, cc[14], r0, r1, d + 1536); epi_group<28, 60>(acc2, cc[15], r0, r1, d + 1792);
                    __syncwarp(); if (lane == 0) mbar_arrive(BAR(B_SIGH + 1)); }
      if (CS_MODE == 0 && s <= 5) ldcs(10 + 2 * s, 12 + 2 * s);
      if (CS_MODE > 0 && s >= 4 && s < 7) ldcs(16 + 2 * (s - 4), 18 + 2 * (s - 4));
      if (s > 0) {
        wg_wait<1>();
        if (lane == 0) { mbar_arrive(BAR(B_EMPTYR + (r - 1) % 6)); if (s < 7) mbar_arrive(emptyA + (s - 1) * 8); }
      }
    }
    STAMP_IF(wl == 0 && lane == 0, TS + 3);
    da = fresh(mkdesc(aw - 16, 1024, 128, 0), p.z64); db = fresh(mkdesc(sb + OFF_RING - 16, 8192, 1024, 1), p.z64);
    float acco[64], base[32];
    {
      mbar_wait(fullA, 1);
      mbar_wait(BAR(B_FULLR), 0);
      wg_fence();
#pragma unroll
      for (int kk = 0; kk < 4; kk++) wgmma_n128<0, 1>(acco, da, 1 + kk * 128, db, 1 + kk * 128, kk != 0);
      wg_commit();
      wg_wait<1>();
      if (lane == 0) {
        mbar_arrive(BAR(B_EMPTYR + 23 % 6));
        asm volatile("mbarrier.arrive.relaxed.cluster.shared::cluster.b64 _, [%0];" :: "r"(mapa(BAR(B_PEER + hw), rank ^ 1)) : "memory");
      }
      reg_fence<0, 48>(acc3);
      uint32_t* d = hdst + (128 + js * 4) * 256;
      uint32_t* dx = hdst + (160 + js * 2) * 256;
      epi_group<0, 16>(acc3, cc[16], r0, r1, d); epi_group<4, 20>(acc3, cc[17], r0, r1, d + 256);
      epi_group<8, 24>(acc3, cc[18], r0, r1, d + 512); epi_group<12, 28>(acc3, cc[19], r0, r1, d + 768);
      if (js < 6) { epi_group<32, 40>(acc3, cc[20], r0, r1, dx); epi_group<36, 44>(acc3, cc[21], r0, r1, dx + 256); }
      __syncwarp();
      if (lane == 0) mbar_arrive(BAR(B_SIGH + 2));
      STAMP_IF(wl == 0 && lane == 0, TS + 4);
#pragma unroll
      for (int s = 1; s < 8; s++) {
        const int slot = s % 6, ps = (s - 1) % 6;
        mbar_wait(fullA + slot * 8, s < 6);
        mbar_wait(BAR(B_FULLR + slot), s >= 6);
        wg_fence();
#pragma unroll
        for (int kk = 0; kk < 4; kk++) wgmma_n128<0, 1>(acco, da, 1 + slot * 512 + kk * 128, db, 1 + slot * 1024 + kk * 128, 1);
        wg_commit();
        if (s == 3) {
          da = fresh(da, p.z64); db = fresh(db, p.z64);
#pragma unroll
          for (int i = 0; i < 16; i++) { base[2 * i] = blo(res[i]); base[2 * i + 1] = bhi(res[i]); }
          reg_fence<0, 32>(base);
        }
        wg_wait<1>();
        if (lane == 0) { mbar_arrive(emptyA + ps * 8); if (s < 6) mbar_arrive(BAR(B_EMPTYR + ps)); }
        STAMP_IF(wl == 0 && lane == 0 && s == 4, TS + 5);
      }
    }
    wg_wait<0>();
    if (lane == 0) mbar_arrive(emptyA + 1 * 8);
    reg_fence<32, 64>(acco);
    reg_rename<0, 32>(acco);
    da = fresh(da, p.z64); db = fresh(db, p.z64);
    STAMP_IF(wl == 0 && lane == 0, TS + 6);
    const uint32_t ob = aw + 6 * 8192 + wl * 4096 + 2048;
    uint32_t oa;
    { const int orow = 2 * (lane & 7) + (((lane >> 3) & 1) ^ 1); oa = ob + orow * 128 + (((lane >> 4) ^ (orow & 7)) * 16); }
    asm volatile("" : "+r"(oa));
    uint32_t ol = ob + (lane >> 3) * 128 + (((lane & 7) ^ (lane >> 3)) * 16);
    uint16_t* og = p.out + (size_t)((blk >> 1) * 128 + (blk & 1) * 8 + wl * 2 + (lane >> 4) * 16 + ((lane >> 3) & 1)) * D_ + js * 64 + (lane & 7) * 8;
    asm volatile("" : "+r"(ol), "+l"(og));
    {
      mbar_wait_cluster(BAR(B_PEER + hw), 0);
      const uint32_t ra = mapa(aw + 6 * 8192 + wl * 4096 + lane * 16, rank ^ 1), rb = mapa(BAR(B_RECV + hw), rank ^ 1);
#pragma unroll
      for (int s = 8; s < 14; s++) {
        const int slot = s % 6, rs = 2 + ((s - 8) >> 1);
        if (s >= SEND_AT && s < SEND_AT + SEND_N) {
#pragma unroll
          for (int i = 4 / SEND_N * (s - SEND_AT); i < 4 / SEND_N * (s - SEND_AT + 1); i++)
            st_async4(ra + i * 512, pack2(acco[32 + 8 * i], acco[33 + 8 * i]), pack2(acco[34 + 8 * i], acco[35 + 8 * i]),
                      pack2(acco[36 + 8 * i], acco[37 + 8 * i]), pack2(acco[38 + 8 * i], acco[39 + 8 * i]), rb);
        }
        mbar_wait(fullA + slot * 8, (s / 6 + 1) & 1);
        if ((s & 1) == 0) mbar_wait(BAR(B_FULLR + rs), 1);
        STAMP_IF(wl == 0 && lane == 0 && s == 8, TS + 7);
        wg_fence();
#pragma unroll
        for (int kk = 0; kk < (s == 13 ? 2 : 4); kk++)
          wgmma_n64<0, 1>(acco, da, 1 + slot * 512 + kk * 128, db, 2049 + (s - 8) * 512 + kk * 128, 1);
        wg_commit();
        if (s == BASE_AT) {
      mbar_wait_cluster(BAR(B_RECV + hw), 0);
      if (lane == 0) mbar_arrive(BAR(B_SIG + 6));
      STAMP_IF(tid == 0, 0);
#pragma unroll
      for (int i = 0; i < 4; i++) {
        const uint4 o = lds128(aw + 6 * 8192 + wl * 4096 + lane * 16 + i * 512);
        const uint32_t ov[4] = {o.x, o.y, o.z, o.w};
#pragma unroll
        for (int j = 0; j < 4; j++) {
          const float hs = (j & 1) ? r1.hs : r0.hs;
          base[8 * i + 2 * j] = fmaf(blo(ov[j]), hs, base[8 * i + 2 * j]); base[8 * i + 2 * j + 1] = fmaf(bhi(ov[j]), hs, base[8 * i + 2 * j + 1]);
        }
      }
      reg_fence<0, 32>(base);
        }
      }
    }
    {
      wg_wait<0>();
      reg_fence<0, 32>(acco);
      STAMP_IF(wl == 0 && lane == 0, TS + 8);
#pragma unroll
      for (int i = 0; i < 32; i++) acco[i] = fmaf(acco[i], (i & 2) ? r1.hs : r0.hs, base[i]);
#pragma unroll
      for (int i = 0; i < 4; i++)
        stsm4(oa ^ (i * 32), pack2(acco[8 * i], acco[8 * i + 1]), pack2(acco[8 * i + 2], acco[8 * i + 3]),
              pack2(acco[8 * i + 4], acco[8 * i + 5]), pack2(acco[8 * i + 6], acco[8 * i + 7]));
      __syncwarp();
#pragma unroll
      for (int i = 0; i < 4; i++) *(uint4*)(og + (size_t)i * 32 * D_) = lds128((ol + i * 512) ^ ((i & 1) * 64));
    }
    STAMP_IF(wl == 0 && lane == 0, TS + 9);
    STAMP_NS(tid == 0, 15);
  } else if (warp < 12) {
    asm volatile("setmaxnreg.dec.sync.aligned.u32 %0;" :: "n"(REG_P));
    const int h = warp - 8;
    const uint4 sk = small;
    const uint32_t w0 = __byte_perm(sk.x, sk.z, 0x5410), w1 = __byte_perm(sk.x, sk.z, 0x7632);
    const uint32_t w2 = __byte_perm(sk.y, sk.w, 0x5410), w3 = __byte_perm(sk.y, sk.w, 0x7632);
    const uint32_t psrc = sb + OFF_KV + 16 + lane * 4 + h * 128;
    const uint32_t pdst = mapa(sb + OFF_U + (q & 1) * 2 * U_PITCH + 32 + rank * 512 + g * 16 + h * 128, q >> 1), pbar = mapa(BAR(B_U), q >> 1);
    asm volatile("barrier.cluster.wait.aligned;" ::: "memory");
#pragma unroll 1
    for (int pc = 0; pc < 4; pc++) {
      mbar_wait(BAR(B_KV + pc), 0);
      SSTAMP(h == 0 && lane == 0, 42 + pc);
      prep_task((q >> 1) == rank, psrc + pc * KV_PIECE, pdst + pc * 1024, pbar + pc * 8, w0, w1, w2, w3);
      __syncwarp();
      if (lane == 0) mbar_arrive(BAR(B_U + pc));
      SSTAMP(h == 0 && lane == 0 && pc == 0, 27);
    }
    __syncwarp();
    if (lane == 0) mbar_arrive(BAR(B_PREPD));
    SSTAMP(h == 0 && lane == 0, 51);
    if (bid < 86) {
      const int which = bid >= 43, unit = bid - which * 43;
      uint32_t wa = sb + OFF_CW + h * 8192 + g * 64 + ((q ^ (g >> 1)) * 16);
      uint16_t* d = p.scr->wX + (size_t)((unit - 40) * 2 + (q >> 1)) * (D_ * 32) + (h * 128 + g) * 32 + ((which * 2 + (q & 1)) ^ (g >> 1)) * 8;
      float cs[8];
#pragma unroll
      for (int i = 0; i < 8; i++) cs[i] = 0.f;
      mbar_wait(BAR(B_CW), 0);
      if (CS_EVT >= 0) mbar_wait(BAR(B_SIGE + CS_EVT), 0);
#pragma unroll 1
      for (int b = 0; b < 4; b++) {
        uint4 v[4];
#pragma unroll
        for (int i = 0; i < 4; i++) v[i] = lds128(wa + i * 512);
#pragma unroll
        for (int i = 0; i < 4; i++) {
          cs[0] += blo(v[i].x); cs[1] += bhi(v[i].x); cs[2] += blo(v[i].y); cs[3] += bhi(v[i].y);
          cs[4] += blo(v[i].z); cs[5] += bhi(v[i].z); cs[6] += blo(v[i].w); cs[7] += bhi(v[i].w);
        }
        if (unit >= 40) {
#pragma unroll
          for (int i = 0; i < 4; i++) *(uint4*)(d + i * 256) = v[i];
        }
        d += 1024; wa += 2048;
      }
#pragma unroll 1
      for (int o = 4; o < 32; o <<= 1)
#pragma unroll
        for (int i = 0; i < 8; i++) cs[i] += __shfl_xor_sync(0xffffffffu, cs[i], o);
      if (lane < 4) {
        sts128f(sb + OFF_CS + h * 128 + lane * 32, cs[0], cs[1], cs[2], cs[3]);
        sts128f(sb + OFF_CS + h * 128 + lane * 32 + 16, cs[4], cs[5], cs[6], cs[7]);
      }
      STAMP_IF(h == 0 && lane == 0, 53);
    }
    __syncwarp();
    if (lane == 0) mbar_arrive(BAR(B_CSD));
    const int ck = rank * 4 + h;
    const uint32_t sdst = mapa(sb + OFF_STX + (ck * 8 + g) * 8, q & 1), sbar = mapa(BAR(B_STX), q & 1);
#pragma unroll 1
    for (int w = 0; w < 2; w++) {
      uint32_t la = sb + OFF_A + w * 65536 + lane * 128 + ((ck ^ (lane & 7)) * 16);
      float s0 = 0.f, s1 = 0.f, q0 = 0.f, q1 = 0.f, c = 0.f;
#pragma unroll 1
      for (int s = 0; s < 8; s++) {
        uint32_t m[8];
        mbar_wait(BAR(B_FULLA + w * 8 + s), 0);
        ldsm4t(la, m[0], m[1], m[2], m[3]); ldsm4t(la + 4096, m[4], m[5], m[6], m[7]);
        la += 8192;
        if (STAT_SHIFT && s == 0) c = __shfl_sync(0xffffffffu, blo(m[0]), lane & ~3);
#pragma unroll
        for (int i = 0; i < 8; i++) {
          float d0 = blo(m[i]), d1 = bhi(m[i]);
          if (STAT_SHIFT) { d0 -= c; d1 -= c; }
          if ((WHATIF & 1024) && i >= 2) continue;
          s0 += d0; s1 += d1; q0 = fmaf(d0, d0, q0); q1 = fmaf(d1, d1, q1);
        }
      }
      s0 += s1; q0 += q1;
#pragma unroll
      for (int o = 1; o < 4; o <<= 1) { s0 += __shfl_xor_sync(0xffffffffu, s0, o); q0 += __shfl_xor_sync(0xffffffffu, q0, o); }
      const float md = s0 * (1.f / D_), var = fmaxf(fmaf(-md, md, q0 * (1.f / D_)), 0.f);
      if (q < 2) asm volatile("st.async.weak.shared::cluster.mbarrier::complete_tx::bytes.v2.f32 [%0], {%1,%2}, [%3];"
                              :: "r"(sdst + w * 512), "f"(-(md + c)), "f"(rsqrtf(var + 1e-5f)), "r"(sbar + w * 8) : "memory");
      STAMP_IF(h == 0 && lane == 0, 46 + w);
    }
  } else {
    asm volatile("setmaxnreg.dec.sync.aligned.u32 %0;" :: "n"(512 - 2 * REG_C - REG_P));
    const int h = warp - 12;
    asm volatile("barrier.cluster.wait.aligned;" ::: "memory");
    if (h == 0) {
      if (elect()) {
#pragma unroll
        for (int pc = 1; pc < 4; pc++) {
          if (pc == KV_HOLD) mbar_wait(BAR(B_GO), 0);
          if (pc == 1 && KV_EVT) mbar_wait(BAR(B_XR), 0);
          if (pc == XS_BEFORE) mbar_wait(BAR(B_XSI), 0);
          if (pc == 3 && KV3_EVT == 1) mbar_wait(BAR(B_KV + 1), 0);
          if (pc == 3 && KV3_EVT == 2) mbar_wait(BAR(B_KV + 2), 0);
          if (pc == 2 && KV_EVT == 1) mbar_wait(BAR(B_KV), 0);
          if (pc == 2 && KV_EVT == 2) mbar_wait(BAR(B_TAP), 0);
          if (pc == 2 && KV_EVT == 3) mbar_wait(BAR(B_U), 0);
          kv_load(pc);
          if (pc == PF_W) {
            asm volatile("cp.async.bulk.prefetch.L2.global [%0], %1;" :: "l"((const char*)p.wg + (size_t)bid * 11008), "r"(11008) : "memory");
            asm volatile("cp.async.bulk.prefetch.L2.global [%0], %1;" :: "l"((const char*)p.wu + (size_t)bid * 11008), "r"(11008) : "memory");
          }
        }
        const int cw = js * 64, c3 = 1024 + js * 32, co = cw ^ 64, kr = rank * 256, b3 = js < 6 ? 12288 : 8192;
        const uint16_t* wx = p.scr->wX + (size_t)js * (D_ * 32);
        if (PRE_EVT != 2) mbar_wait(BAR(B_GO), 0);
        if (PF_W == 4) {
          asm volatile("cp.async.bulk.prefetch.L2.global [%0], %1;" :: "l"((const char*)p.wg + (size_t)bid * 11008), "r"(11008) : "memory");
          asm volatile("cp.async.bulk.prefetch.L2.global [%0], %1;" :: "l"((const char*)p.wu + (size_t)bid * 11008), "r"(11008) : "memory");
        }
        if (PRE_EVT == 0) mbar_wait(BAR(B_KV + 3), 0);
        if (PRE_EVT == 2) mbar_wait(BAR(B_KV + 2), 0);
        if (PRE_EVT == 3) mbar_wait(BAR(B_XT), 0);
        const uint16_t* hs0 = p.scr->H + (size_t)tile * (86 * 1024);
        const uint16_t* hp0 = hs0 + rank * 16384;
        static_for<0, SCHED_N>([&](auto ic) {
          constexpr int it = decltype(ic)::v, r = SCHED[it];
          if constexpr (r == 2 && PRE_EVT == 2) mbar_wait(BAR(B_GO), 0);
          if constexpr (r == CW_AT) {
            if (bid < 86) {
              mbar_wait(BAR(B_PREPD), 0);
              fence_async_s();
              mbar_expect(BAR(B_CW), 32768);
#pragma unroll 1
              for (int i = 0; i < 8; i++) tma2d(sb + OFF_CW + i * 4096, bid >= 43 ? &tmU32 : &tmG32, (bid >= 43 ? bid - 43 : bid) * 32, i * 64, BAR(B_CW));
            }
            STAMP(28);
          }
          if constexpr (r == 3) {
            mbar_wait(BAR(R3_EVT ? B_SIGE + 1 : B_GO + 1), 0);
            fence_async_s();
            if (R_AFTER_A >= 0) mbar_wait(BAR(B_FULLA + R_AFTER_A), 0);
          }
          if constexpr (r == PF_D) asm volatile("cp.async.bulk.prefetch.L2.global [%0], %1;" :: "l"((const char*)p.wd + (size_t)bid * 11008), "r"(11008) : "memory");
          if constexpr (r == 16) mbar_wait(BAR(B_CS), 0);
          if constexpr (OUT_TMA && r == 33) asm volatile("prefetch.tensormap [%0];" :: "l"(&tmO) : "memory");
          constexpr int w = r & 1, hs = (r - 64) >> 1;
          if constexpr (r >= 64) {
            if constexpr (w == 0 && (hs & 3) == 0 && hs < 12) { mbar_wait(BAR(B_SEEN + (hs >> 2)), 0); fence_async_g(); }
            mbar_wait(BAR(B_EMPTYA + w * 6 + hs % 6), (hs / 6) & 1);
          } else if constexpr (r >= 6) mbar_wait(BAR(B_EMPTYR + r % 6), (r / 6 - 1) & 1);
          static_for<SchedDep<it - 1>::v + 1, SchedDep<it>::v + 1>([&](auto jc) {
            constexpr int j = decltype(jc)::v, o = SCHED[j], os = (o - 64) >> 1;
            if constexpr (!SchedReused<j, it>::v) {
              if constexpr (o < 64) mbar_wait(BAR(B_FULLR + o % 6), (o / 6) & 1);
              else mbar_wait(BAR(B_FULLA + (o & 1) * 8 + os % 6), (os / 6 + 1) & 1);
            }
          });
          const uint32_t b = BAR(B_FULLR + r % 6), d = sb + OFF_RING + (r % 6) * 16384;
          if constexpr (r >= 64) {
            const uint32_t fb = BAR(B_FULLA + w * 8 + hs % 6);
            mbar_expect(fb, hs == 13 ? 4096 : 8192);
            bulk_ld(sb + OFF_A + w * 65536 + (hs % 6) * 8192,
                    (hs < 8 ? hp0 + ((hs & 4) * 2 + (hs & 3)) * 4096 : hs0 + (hs + 8) * 4096) + (size_t)w * (16 * 86 * 1024), hs == 13 ? 4096 : 8192, fb);
          } else if constexpr (r < 16) {
            mbar_expect(b, 16384);
            tma2d(d, &tmG, cw + (r >> 3) * 512, (r & 7) * 64, b); tma2d(d + 8192, &tmU, cw + (r >> 3) * 512, (r & 7) * 64, b);
          } else if constexpr (r < 24) {
            mbar_expect(b, b3);
            tma2d(d, &tmG32, c3, (r & 7) * 64, b); tma2d(d + 4096, &tmU32, c3, (r & 7) * 64, b);
            if (js < 6) bulk_ld(d + 8192, wx + (r & 7) * 2048, 4096, b);
          } else if constexpr (r < 32) {
            const int k = kr + ((r & 4) * 2 + (r & 3)) * 64;
            mbar_expect(b, 16384);
            tma2d(d, &tmD, cw, k, b); tma2d(d + 8192, &tmD, co, k, b);
          } else {
            mbar_expect(b, 16384);
            tma2d(d, &tmD, cw, 1024 + (r - 32) * 128, b); tma2d(d + 8192, &tmD, cw, 1088 + (r - 32) * 128, b);
          }
        });
        p.scr->epoch[bid] = small.x + 1;
      }
    } else if (h == 3) {
      mbar_wait_bounded(BAR(X_SPLIT ? B_SIGT : B_SIGX), 0);
      fence_async_s();
      if (elect()) {
        asm volatile("cp.async.bulk.tensor.2d.global.shared::cta.bulk_group [%0, {%2, %3}], [%1];" :: "l"(&tmX), "r"(sb + OFF_XST), "r"(xb * 64), "r"(0) : "memory");
        mbar_arrive(BAR(B_XSI));
      }
      __syncwarp();
#pragma unroll 1
      for (int i = 0; i < 7; i++) {
        mbar_wait_bounded(BAR(B_SIG + i), 0);
        if (i == 6) break;
        if (SIG2 && i == 1) continue;
        unsigned* c = &p.scr->cnt[(i < 3 ? i : CNT_H + tile * 3 + i - 3) * 32];
        if (i == 0) {
          fence_async_s();
          if (elect()) {
            asm volatile("cp.async.bulk.global.shared::cta.bulk_group [%0], [%1], 64;" :: "l"(p.scr->st1 + xb * 16), "r"(sb + OFF_CS) : "memory");
            asm volatile("cp.async.bulk.commit_group;" ::: "memory");
            asm volatile("cp.async.bulk.wait_group 0;" ::: "memory");
          }
          __syncwarp();
        }
        if (lane == 0) { if (((WHATIF & 2) && i >= 3) || ((WHATIF & 16) && i > 0 && i < 3) || ((WHATIF & 64) && i == 0)) asm volatile("red.relaxed.gpu.global.add.u32 [%0], 1;" :: "l"(c) : "memory"); else signal_gpu(c); if (i == 0 || i == 2) mbar_arrive(BAR(B_GO + (i >> 1))); }
        __syncwarp();
        STAMP_IF(lane == 0, i == 0 ? 50 : 53 + i);
        if (i == 2 && bid < 86) {
          const int which = bid >= 43, f = (bid - which * 43) * 32 + lane;
          mbar_wait_bounded(BAR(B_CSD), 0);
          const uint32_t a = sb + OFF_CS + lane * 4;
          const float sum = __uint_as_float(lds32(a)) + __uint_as_float(lds32(a + 128)) + __uint_as_float(lds32(a + 256)) + __uint_as_float(lds32(a + 384));
          const uint32_t lo = __shfl_up_sync(0xffffffffu, pack2(sum, 0.f), 1), sb_ = __float_as_uint(sum);
          const uint32_t hi = (sb_ & 0x7fffffffu) < 0x10000u ? sb_ : sb_ - lo + 0x8000u;
          if (lane & 1) p.scr->cs[(f >> 4) * 16 + ((f >> 1) & 3) * 4 + ((f >> 3) & 1) * 2 + which] = __uint_as_float((hi & 0xffff0000u) | lo);
          __syncwarp();
          if (lane == 0) signal_gpu(&p.scr->cnt[CNT_C * 32]);
          __syncwarp();
          STAMP_IF(lane == 0, 29);
        }
      }
    } else {
      const unsigned ep = small.x + 1;
      const int w = h - 1, blk = tile + 16 * w;
      const uint32_t aw = sb + OFF_A + w * 65536;
      const uint32_t fullA = BAR(B_FULLA + w * 8);
      if (elect()) {
        if (w == 0) {
          mbar_wait(BAR(B_GO), 0);
          poll1(&p.scr->cnt[CNT_X * 32], ep * NCTA);
          fence_async_g(); fence_async_s();
          uint32_t b = BAR(B_XT);
          mbar_expect(b, 12288); mbar_expect(b + 8, 12288);
          bulk_ld(sb + OFF_XTE, p.scr->xT + (size_t)bid * 8192, 8192, b);
          bulk_ld(sb + OFF_STE, p.scr->st1, 4096, b);
          bulk_ld(sb + OFF_XTL, p.scr->xT + (size_t)bid * 8192 + 4096, 8192, b + 8);
          bulk_ld(sb + OFF_STL, p.scr->st1 + 1024, 4096, b + 8);
          SSTAMP(true, 52);
        }
      const uint16_t* asrc = p.scr->hT + (size_t)blk * (D_ * 64);
      const unsigned* hc = &p.scr->cnt[(CNT_H + tile * 3) * 32];
        if (SIG2 && w == 1) { mbar_wait(BAR(B_SIGE), 0); signal_gpu(&p.scr->cnt[CNT_E * 32]); STAMP(54); }
        mbar_wait(w ? BAR(B_GO + 1) : BAR(B_SIGE), 0);
        fence_async_s();
        if (!(WHATIF & 8)) poll1(&p.scr->cnt[(CNT_E + w) * 32], ep * NCTA);
        STAMP(59 + w);
        if (A_AFTER_GO) mbar_wait(BAR(B_GO + 1), 0);
        fence_async_g();
#pragma unroll
        for (int s = 0; s < 8; s++) {
          if (s == 3 && w == 0) { mbar_wait(BAR(B_CSD), 0); fence_async_s(); }
          if (s >= A_DEPTH0 && w == 0) mbar_wait(fullA + (s - A_DEPTH0) * 8, 0);
          if (s >= A_DEPTH && w == 1) mbar_wait(fullA + (s - A_DEPTH) * 8, 0);
          mbar_expect(fullA + s * 8, 8192);
          bulk_ld(aw + s * 8192, asrc + s * 4096, 8192, fullA + s * 8);
        }
        if (w == 0) {
          poll1(&p.scr->cnt[CNT_C * 32], ep * 86);
          fence_async_g(); fence_async_s();
          uint32_t b = BAR(B_CS), d = sb + OFF_CS;
          constexpr int CW = CS_PACK ? 1 : 2;
          mbar_expect(b, (js < 6 ? 704 : 640) * CW);
          bulk_ld(d, p.scr->cs + js * 64 * CW, 256 * CW, b);
          bulk_ld(d + 256 * CW, p.scr->cs + (512 + js * 64) * CW, 256 * CW, b);
          bulk_ld(d + 512 * CW, p.scr->cs + (1024 + js * 32) * CW, 128 * CW, b);
          if (js < 6) bulk_ld(d + 640 * CW, p.scr->cs + (1280 + js * 16) * CW, 64 * CW, b);
          STAMP(30);
        }
        if (w == 1) {
#pragma unroll 1
          for (int c = 0; c < 3; c++) {
            if (!(WHATIF & 4)) { mbar_wait(BAR(B_SIGH + c), 0);
            poll1(hc + c * 32, ep * 8); }
            mbar_arrive(BAR(B_SEEN + c));
            STAMP(61 + c);
          }
        }
      }
    }
  }
}

typedef CUresult (*EncFn)(CUtensorMap*, CUtensorMapDataType, cuuint32_t, void*, const cuuint64_t*, const cuuint64_t*,
                          const cuuint32_t*, const cuuint32_t*, CUtensorMapInterleave, CUtensorMapSwizzle,
                          CUtensorMapL2promotion, CUtensorMapFloatOOBfill);

void make_map(EncFn fn, CUtensorMap* tm, const void* ptr, int w, int hgt, int bw, int bh, CUtensorMapSwizzle sw, CUtensorMapL2promotion pr) {
  cuuint64_t dims[2] = {(cuuint64_t)w, (cuuint64_t)hgt};
  cuuint64_t str[1] = {(cuuint64_t)w * 2};
  cuuint32_t box[2] = {(cuuint32_t)bw, (cuuint32_t)bh}, es[2] = {1, 1};
  fn(tm, CU_TENSOR_MAP_DATA_TYPE_BFLOAT16, 2, (void*)ptr, dims, str, box, es, CU_TENSOR_MAP_INTERLEAVE_NONE, sw, pr,
     CU_TENSOR_MAP_FLOAT_OOB_FILL_NONE);
}

void make_map_runs(EncFn fn, CUtensorMap* tm, const void* ptr) {
  cuuint64_t dims[3] = {(cuuint64_t)D_, (cuuint64_t)(S_ / 8), 8};
  cuuint64_t str[2] = {(cuuint64_t)D_ * 16, (cuuint64_t)D_ * 2};
  cuuint32_t box[3] = {8, 33, 8}, es[3] = {1, 1, 1};
  fn(tm, CU_TENSOR_MAP_DATA_TYPE_BFLOAT16, 3, (void*)ptr, dims, str, box, es, CU_TENSOR_MAP_INTERLEAVE_NONE,
     CU_TENSOR_MAP_SWIZZLE_NONE, CU_TENSOR_MAP_L2_PROMOTION_L2_128B, CU_TENSOR_MAP_FLOAT_OOB_FILL_NONE);
}

}

extern "C" void kernel_launch(void* const* d_in, const int* in_sizes, int n_in, void* d_out, int out_size) {
  (void)in_sizes; (void)n_in; (void)out_size;
  static EncFn fn = nullptr;
  if (!fn) {
    void* f = nullptr; cudaDriverEntryPointQueryResult qr;
    cudaGetDriverEntryPoint("cuTensorMapEncodeTiled", &f, cudaEnableDefault, &qr);
    fn = (EncFn)f;
    cudaFuncSetAttribute(fused_kernel, cudaFuncAttributeMaxDynamicSharedMemorySize, SMEM_BYTES);
  }
  CUtensorMap tmK, tmV, tmG, tmU, tmG32, tmU32, tmD, tmX, tmXR, tmT, tmO;
  void* xT = nullptr;
  cudaGetSymbolAddress(&xT, g_scr);
  make_map(fn, &tmX, xT, 8192, 128, 64, 128, CU_TENSOR_MAP_SWIZZLE_NONE, CU_TENSOR_MAP_L2_PROMOTION_NONE);
  {
    cuuint64_t dims[3] = {128, 16, (cuuint64_t)D_}, str[2] = {256, (cuuint64_t)S_ * 2};
    cuuint32_t box[3] = {128, 17, 2}, es[4] = {1, 1, 1, 1};
    fn(&tmT, CU_TENSOR_MAP_DATA_TYPE_BFLOAT16, 3, d_in[4], dims, str, box, es, CU_TENSOR_MAP_INTERLEAVE_NONE,
       CU_TENSOR_MAP_SWIZZLE_NONE, CU_TENSOR_MAP_L2_PROMOTION_NONE, CU_TENSOR_MAP_FLOAT_OOB_FILL_NONE);
    cuuint64_t dimso[3] = {(cuuint64_t)D_, 16, 128}, stro[2] = {1024, 16384};
    cuuint32_t boxo[3] = {64, 2, 8};
    fn(&tmO, CU_TENSOR_MAP_DATA_TYPE_BFLOAT16, 3, d_out, dimso, stro, boxo, es, CU_TENSOR_MAP_INTERLEAVE_NONE,
       CU_TENSOR_MAP_SWIZZLE_128B, CU_TENSOR_MAP_L2_PROMOTION_NONE, CU_TENSOR_MAP_FLOAT_OOB_FILL_NONE);
    cuuint64_t dims4[4] = {64, 16, 128, 8}, str4[3] = {1024, 16384, 128};
    cuuint32_t box4[4] = {64, 2, 8, 8};
    fn(&tmXR, CU_TENSOR_MAP_DATA_TYPE_BFLOAT16, 4, d_in[0], dims4, str4, box4, es, CU_TENSOR_MAP_INTERLEAVE_NONE,
       CU_TENSOR_MAP_SWIZZLE_128B, CU_TENSOR_MAP_L2_PROMOTION_L2_256B, CU_TENSOR_MAP_FLOAT_OOB_FILL_NONE);
  }
  make_map_runs(fn, &tmK, d_in[1]);
  make_map_runs(fn, &tmV, d_in[2]);
  make_map(fn, &tmG, d_in[7], F_, D_, 64, 64, CU_TENSOR_MAP_SWIZZLE_128B, CU_TENSOR_MAP_L2_PROMOTION_NONE);
  make_map(fn, &tmU, d_in[8], F_, D_, 64, 64, CU_TENSOR_MAP_SWIZZLE_128B, CU_TENSOR_MAP_L2_PROMOTION_NONE);
  make_map(fn, &tmG32, d_in[7], F_, D_, 32, 64, CU_TENSOR_MAP_SWIZZLE_64B, CU_TENSOR_MAP_L2_PROMOTION_NONE);
  make_map(fn, &tmU32, d_in[8], F_, D_, 32, 64, CU_TENSOR_MAP_SWIZZLE_64B, CU_TENSOR_MAP_L2_PROMOTION_NONE);
  make_map(fn, &tmD, d_in[9], D_, F_, 64, 64, CU_TENSOR_MAP_SWIZZLE_128B, CU_TENSOR_MAP_L2_PROMOTION_NONE);
  Params p;
  p.x = (const uint16_t*)d_in[0]; p.shift_k = (const uint16_t*)d_in[3]; p.ssm_k = (const uint16_t*)d_in[4];
  p.ssm_D = (const uint16_t*)d_in[5]; p.wg = (const uint16_t*)d_in[7]; p.wu = (const uint16_t*)d_in[8];
  p.wd = (const uint16_t*)d_in[9]; p.out = (uint16_t*)d_out; p.scr = (Scratch*)xT; p.z64 = 0;
  cudaLaunchConfig_t cfg = {};
  cfg.gridDim = dim3(NCTA); cfg.blockDim = dim3(NTHR); cfg.dynamicSmemBytes = SMEM_BYTES; cfg.stream = cudaStreamPerThread;
  cudaLaunchAttribute at[1];
  at[0].id = cudaLaunchAttributeClusterDimension; at[0].val.clusterDim.x = 2; at[0].val.clusterDim.y = 1; at[0].val.clusterDim.z = 1;
  cfg.attrs = at; cfg.numAttrs = 1;
  cudaLaunchKernelEx(&cfg, fused_kernel, p, tmXR, tmT, tmK, tmV, tmG, tmU, tmG32, tmU32, tmD, tmX, tmO);
}
```

```cpp
#include <cuda_runtime.h>
#include <cuda_bf16.h>
#include <cuda.h>
#include <stdint.h>

namespace {

constexpr int S_ = 2048, D_ = 512, F_ = 1376;
constexpr int NCTA = 128, NTHR = 512;
#define STAT_SHIFT 0
#define CONV_ORDER 0
#define CONV_TAIL 0
#define PREP_FMA 1
#define KV_EVT 2
#define A_AFTER_GO 0
#define A_DEPTH0 4
#define R_AFTER_A 3
#define WIN 72
#define WIN3 200
#define BASE_AT 13
#define ORD 5
#define W3_FROM 46
#define W2_FROM 36
#define WINA WIN
#define WARM 1
#define RED_H2 0
#define XS_BEFORE 0
#define KV3_EVT 0
#define X_SPLIT 0
#define WHATIF 0
#define WIN0 32
#define WINE 32
#define WINC 36
#define WE_TO 6
#define PF_W 0
#define PF_D 10
#define PRE_EVT 0
#define CW_AT 3
#define R3_EVT 0
#define CS_EVT 1
#define SIG2 1
#define REG_C 216
#define REG_P 48
#define STX_AT 0
#define NOF 7
#define PRO_TAB 0
#define EPI1 0x44332211
#define EPI2 0x33221100
#define EPI3B 0
#define EPI3C 0
#define RES_AT 5
#define CS3_AT 4
#define NCS 110
#define C_BY_PREP 0
#define P1 -1
#define P2 -1
#define ARRH 1
#define X_DRY 1
#define P_DRY 1
#define X_1PASS 1
#define PROMO_W 0
#define PROMO_W32 3
#define PROMO_X 3
#define SEND_AT 8
#define OWN_AT 10
#define KV_HOLD 0

#define A_DEPTH 2
#define WIN1 36

struct __align__(1024) Scratch {
  uint16_t xT[D_ * S_];
  uint16_t hT[32 * D_ * 64];
  uint16_t H[32 * 86 * 1024];
  uint16_t wX[6 * D_ * 32];
  uint32_t st1[S_];
  uint32_t cs[F_];
  unsigned cnt[(4 + 48) * 32];
  unsigned epoch[NCTA];
};
__device__ Scratch g_scr;
#define STAMP(id)
#define STAMP_IF(c, id)
#define SSTAMP(c, id)
#define STAMP_NS(c, id)
constexpr int CNT_X = 0, CNT_E = 1, CNT_C = 3, CNT_H = 4;
__host__ __device__ constexpr int tok(int b, int tau) { return 128 * (b >> 1) + 16 * (tau & 7) + 8 * (b & 1) + ((tau >> 3) ^ 1); }

constexpr uint32_t OFF_A    = 0;
constexpr uint32_t OFF_RING = 131072;
constexpr uint32_t OFF_CS   = 229376;
constexpr uint32_t OFF_SK   = OFF_CS + 1024;
constexpr uint32_t OFF_BAR  = OFF_CS + 1408;
constexpr uint32_t OFF_STX  = OFF_BAR + 640;
constexpr uint32_t SMEM_BYTES = 232448;
constexpr uint32_t KV_PIECE = 8448;
constexpr uint32_t OFF_KV   = 65536 - 4 * KV_PIECE;
constexpr uint32_t OFF_CW   = 32768;
constexpr uint32_t OFF_XR   = 0;
constexpr uint32_t OFF_XTE  = OFF_XR;
constexpr uint32_t OFF_STE  = OFF_XR + 8192;
constexpr uint32_t U_PITCH  = 8352, U_ODD = 4160;
constexpr uint32_t T_PITCH  = 4352;
constexpr uint32_t OFF_TAP  = 65536;
constexpr uint32_t OFF_U    = OFF_TAP + 4 * T_PITCH;
constexpr uint32_t OFF_XTL  = OFF_U + 4 * U_PITCH;
constexpr uint32_t OFF_STL  = OFF_XTL + 8192;
constexpr uint32_t OFF_XST  = OFF_RING + 2 * 16384;
constexpr uint32_t OFF_XCH  = OFF_RING + 3 * 16384;
static_assert(OFF_XR % 1024 == 0 && OFF_XR + 16384 <= 65536, "");
static_assert(OFF_STL + 4096 <= 131072, "");
static_assert(OFF_STX + 1024 <= SMEM_BYTES, "");
constexpr int B_EMPTYR = 0  , B_SIG = 6  , B_SIGT = 13,
              B_EMPTYA = 20  , B_PEER = 32  , B_PREPD = 34, B_CSD = 35, B_GOH = 36  , B_XSI = 39  ,
              B_KV = 40  , B_XR = 44, B_TAP = 45  , B_CS = 47, B_GO = 48  ,
              B_U = 50  , B_RECV = 54  , B_STX = 56  , B_XT = 58  , B_FULLA = 60  , B_CW = 76, B_SEEN = 77  ,
              B_FULLR = 14  ;
constexpr int B_SK = -1, B_SIGX = B_SIG, B_SIGE = B_SIG + 1, B_SIGH = B_SIG + 3;

#define HH(s) 64 + 2 * (s), 65 + 2 * (s)
constexpr int SCHED_N = 22 + 13 + 24;
constexpr int SCHED[SCHED_N] = {0, 1, 2, 3, 4, 5, 6, 7, 8, 9, 10, 11, 12, 13, 14, 15, 16, 17, 18, 19, 20, 21,
  22, 23, HH(0), 24, HH(1), 25, HH(2), 26, 27, 28, 29, 30, HH(3), 31, HH(4), HH(5), 32, 33,
  HH(6), HH(7), HH(8), HH(9), 34, HH(10), HH(11)};
__host__ __device__ constexpr int h_slot(int s) { return s < 6 ? s : s < 9 ? s - 6 : s == 9 ? 7 : s - 7; }
__host__ __device__ constexpr int h_par(int s) { return s < 6 || s == 9; }
constexpr int sched_kb(int v) { return v >= 64 ? 8 : v >= 16 && v < 24 ? 12 : 16; }
constexpr int sched_dep(int i) {
  int best = -1;
  for (int k = 0; k <= i; k++) {
    int acc = 0, win = k < 3 ? WIN0 : k < WE_TO ? WINE : k < 16 ? WIN1 : k < 22 ? WINC : (k >= W3_FROM ? WIN3 : k >= W2_FROM ? WIN : WINA);
    for (int j = k; j >= 0; j--) { acc += sched_kb(SCHED[j]); if (acc > win) { if (j > best) best = j; break; } }
  }
  return best;
}
constexpr bool sched_reused(int j, int i) {
  for (int k = j + 1; k <= i; k++) {
    const int a = SCHED[j], b = SCHED[k];
    if (a < 64 ? b == a + 6 : (b >= 64 && !((a ^ b) & 1) && h_slot((a - 64) >> 1) == h_slot((b - 64) >> 1))) return true;
  }
  return false;
}
template <int I> struct SchedDep { static constexpr int v = sched_dep(I); };
template <int J, int I> struct SchedReused { static constexpr bool v = sched_reused(J, I); };
template <int I> struct IC { static constexpr int v = I; };
template <int I, int E, class F> __device__ __forceinline__ void static_for(F&& f) { if constexpr (I < E) { f(IC<I>{}); static_for<I + 1, E>(f); } }

__device__ __forceinline__ uint32_t s2u(const void* p) { return (uint32_t)__cvta_generic_to_shared(p); }
__device__ __forceinline__ void mbar_init(uint32_t b, int n) { asm volatile("mbarrier.init.shared::cta.b64 [%0], %1;" :: "r"(b), "r"(n) : "memory"); }
__device__ __forceinline__ void mbar_expect(uint32_t b, int bytes) { asm volatile("mbarrier.arrive.expect_tx.shared::cta.b64 _, [%0], %1;" :: "r"(b), "r"(bytes) : "memory"); }
__device__ __forceinline__ void mbar_arrive(uint32_t b) { asm volatile("mbarrier.arrive.shared::cta.b64 _, [%0];" :: "r"(b) : "memory"); }
#define MBAR_WAIT_ASM(SEM) \
  asm volatile("{\n .reg .pred p;\nSPIN:\n mbarrier.try_wait.parity" SEM ".shared::cta.b64 p, [%0], %1;\n @!p bra SPIN;\n}" :: "r"(b), "r"(par) : "memory")
__device__ __forceinline__ void mbar_wait(uint32_t b, int par) { MBAR_WAIT_ASM(""); }
__device__ __forceinline__ void mbar_wait_cluster(uint32_t b, int par) {
  MBAR_WAIT_ASM("");
  asm volatile("fence.acquire.sync_restrict::shared::cluster.cluster;" ::: "memory");
}
__device__ __forceinline__ void mbar_wait_bounded(uint32_t b, int par) {
  asm volatile("{\n .reg .pred p, t; .reg .u32 c;\n mov.u32 c, 0;\n"
    "SPIN:\n mbarrier.try_wait.parity.shared::cta.b64 p, [%0], %1;\n @p bra DONE;\n"
    " add.u32 c, c, 1;\n setp.lt.u32 t, c, 1048576;\n @t bra SPIN;\n trap;\nDONE:\n}" :: "r"(b), "r"(par) : "memory");
}
__device__ __forceinline__ uint32_t mapa(uint32_t a, int r) { uint32_t d; asm("mapa.shared::cluster.u32 %0, %1, %2;" : "=r"(d) : "r"(a), "r"(r)); return d; }
__device__ __forceinline__ void st_async4(uint32_t a, uint32_t x, uint32_t y, uint32_t z, uint32_t w, uint32_t bar) {
  asm volatile("st.async.weak.shared::cluster.mbarrier::complete_tx::bytes.v4.b32 [%0], {%1,%2,%3,%4}, [%5];" :: "r"(a), "r"(x), "r"(y), "r"(z), "r"(w), "r"(bar) : "memory");
}
__device__ __forceinline__ void tma3d(uint32_t dst, const CUtensorMap* tm, int c0, int c1, int c2, uint32_t bar) {
  asm volatile("cp.async.bulk.tensor.3d.shared::cluster.global.mbarrier::complete_tx::bytes [%0], [%1, {%3, %4, %5}], [%2];" :: "r"(dst), "l"(tm), "r"(bar), "r"(c0), "r"(c1), "r"(c2) : "memory");
}
__device__ __forceinline__ void sts64(uint32_t a, uint32_t x, uint32_t y) { asm volatile("st.shared.v2.b32 [%0], {%1,%2};" :: "r"(a), "r"(x), "r"(y) : "memory"); }
__device__ __forceinline__ bool elect() { uint32_t p; asm volatile("{ .reg .pred P; elect.sync _|P, 0xffffffff; selp.u32 %0, 1, 0, P; }" : "=r"(p)); return p; }
__device__ __forceinline__ void bulk_ld(uint32_t dst, const void* src, int bytes, uint32_t bar) {
  asm volatile("cp.async.bulk.shared::cluster.global.mbarrier::complete_tx::bytes [%0], [%1], %2, [%3];" :: "r"(dst), "l"(src), "r"(bytes), "r"(bar) : "memory");
}
__device__ __forceinline__ void tma2d(uint32_t dst, const CUtensorMap* tm, int c0, int c1, uint32_t bar) {
  asm volatile("cp.async.bulk.tensor.2d.shared::cluster.global.mbarrier::complete_tx::bytes [%0], [%1, {%3, %4}], [%2];" :: "r"(dst), "l"(tm), "r"(bar), "r"(c0), "r"(c1) : "memory");
}
__device__ __forceinline__ void fence_async_g() { asm volatile("fence.proxy.async.global;" ::: "memory"); }
__device__ __forceinline__ void fence_async_s() { asm volatile("fence.proxy.async.shared::cta;" ::: "memory"); }
__device__ __forceinline__ void poll1(const unsigned* p, unsigned target) {
  unsigned v;
  do { asm volatile("ld.relaxed.gpu.global.u32 %0, [%1];" : "=r"(v) : "l"(p) : "memory"); } while ((int)(v - target) < 0);
  asm volatile("fence.acquire.gpu;" ::: "memory");
}
__device__ __forceinline__ void signal_gpu(unsigned* p) {
  fence_async_g();
  asm volatile("red.release.gpu.global.add.u32 [%0], 1;" :: "l"(p) : "memory");
}
__device__ __forceinline__ void bar_sync(int id, int n) { asm volatile("bar.sync %0, %1;" :: "r"(id), "r"(n) : "memory"); }
__device__ __forceinline__ uint32_t lds32(uint32_t a) { uint32_t v; asm volatile("ld.shared.b32 %0, [%1];" : "=r"(v) : "r"(a)); return v; }
__device__ __forceinline__ uint2 lds64(uint32_t a) { uint2 v; asm volatile("ld.shared.v2.b32 {%0,%1}, [%2];" : "=r"(v.x), "=r"(v.y) : "r"(a)); return v; }
__device__ __forceinline__ uint4 lds128(uint32_t a) { uint4 v; asm volatile("ld.shared.v4.b32 {%0,%1,%2,%3}, [%4];" : "=r"(v.x), "=r"(v.y), "=r"(v.z), "=r"(v.w) : "r"(a)); return v; }
__device__ __forceinline__ float4 lds128f(uint32_t a) { float4 v; asm volatile("ld.shared.v4.f32 {%0,%1,%2,%3}, [%4];" : "=f"(v.x), "=f"(v.y), "=f"(v.z), "=f"(v.w) : "r"(a)); return v; }
__device__ __forceinline__ void sts32(uint32_t a, uint32_t v) { asm volatile("st.shared.b32 [%0], %1;" :: "r"(a), "r"(v) : "memory"); }
__device__ __forceinline__ void sts128f(uint32_t a, float x, float y, float z, float w) { asm volatile("st.shared.v4.f32 [%0], {%1,%2,%3,%4};" :: "r"(a), "f"(x), "f"(y), "f"(z), "f"(w) : "memory"); }
__device__ __forceinline__ void ldsm4t(uint32_t a, uint32_t& r0, uint32_t& r1, uint32_t& r2, uint32_t& r3) {
  asm volatile("ldmatrix.sync.aligned.m8n8.x4.trans.shared.b16 {%0,%1,%2,%3}, [%4];" : "=r"(r0), "=r"(r1), "=r"(r2), "=r"(r3) : "r"(a));
}
__device__ __forceinline__ void stsm4(uint32_t a, uint32_t r0, uint32_t r1, uint32_t r2, uint32_t r3) {
  asm volatile("stmatrix.sync.aligned.m8n8.x4.shared.b16 [%0], {%1,%2,%3,%4};" :: "r"(a), "r"(r0), "r"(r1), "r"(r2), "r"(r3) : "memory");
}
__device__ __forceinline__ uint32_t bmul(uint32_t a, uint32_t b) { uint32_t d; asm("mul.rn.bf16x2 %0, %1, %2;" : "=r"(d) : "r"(a), "r"(b)); return d; }
__device__ __forceinline__ uint32_t badd(uint32_t a, uint32_t b) { uint32_t d; asm("add.rn.bf16x2 %0, %1, %2;" : "=r"(d) : "r"(a), "r"(b)); return d; }
__device__ __forceinline__ uint32_t bfma(uint32_t a, uint32_t b, uint32_t c) { uint32_t d; asm("fma.rn.bf16x2 %0, %1, %2, %3;" : "=r"(d) : "r"(a), "r"(b), "r"(c)); return d; }
__device__ __forceinline__ float blo(uint32_t v) { return __uint_as_float(v << 16); }
__device__ __forceinline__ float bhi(uint32_t v) { return __uint_as_float(v & 0xffff0000u); }
__device__ __forceinline__ uint32_t pack2(float lo, float hi) { uint32_t d; asm("cvt.rn.bf16x2.f32 %0, %1, %2;" : "=r"(d) : "f"(hi), "f"(lo)); return d; }
__device__ __forceinline__ uint64_t mkdesc(uint32_t addr, uint32_t lbo, uint32_t sbo, int swz) {
  return (uint64_t)((addr & 0x3FFFF) >> 4) | ((uint64_t)(lbo >> 4) << 16) | ((uint64_t)(sbo >> 4) << 32) | ((uint64_t)swz << 62);
}
__device__ __forceinline__ void wg_fence() { asm volatile("wgmma.fence.sync.aligned;" ::: "memory"); }
__device__ __forceinline__ void wg_commit() { asm volatile("wgmma.commit_group.sync.aligned;" ::: "memory"); }
template <int N> __device__ __forceinline__ void wg_wait() { asm volatile("wgmma.wait_group.sync.aligned %0;" :: "n"(N) : "memory"); }
template <int I0, int I1, int N> __device__ __forceinline__ void reg_fence(float (&d)[N]) {
#pragma unroll
  for (int i = I0; i < I1; i++) asm volatile("" : "+f"(d[i]) :: "memory");
}
template <int I0, int I1, int N> __device__ __forceinline__ void reg_rename(float (&d)[N]) {
#pragma unroll
  for (int i = I0; i < I1; i++) { float t; asm volatile("mov.b32 %0, %1;" : "=f"(t) : "f"(d[i]) : "memory"); d[i] = t; }
}
__device__ __forceinline__ uint64_t fresh(uint64_t d, uint64_t z) { asm volatile("add.u64 %0, %0, %1;" : "+l"(d) : "l"(z)); return d; }
template <int TA, int TB, int SZ>
__device__ __forceinline__ void wgmma_n64(float (&d)[SZ], uint64_t a, uint64_t ao, uint64_t b, uint64_t bo, int sd) {
  asm volatile("{ .reg .pred p; .reg .b64 da, db; setp.ne.b32 p, %36, 0; add.u64 da, %32, %33; add.u64 db, %34, %35;\n"
    "wgmma.mma_async.sync.aligned.m64n64k16.f32.bf16.bf16 {%0, %1, %2, %3, %4, %5, %6, %7, %8, %9, %10, %11, %12, %13, %14, %15, %16, %17, %18, %19, %20, %21, %22, %23, %24, %25, %26, %27, %28, %29, %30, %31}, da, db, p, 1, 1, %37, %38; }"
    : "+f"(d[0]), "+f"(d[1]), "+f"(d[2]), "+f"(d[3]), "+f"(d[4]), "+f"(d[5]), "+f"(d[6]), "+f"(d[7]), "+f"(d[8]), "+f"(d[9]), "+f"(d[10]), "+f"(d[11]), "+f"(d[12]), "+f"(d[13]), "+f"(d[14]), "+f"(d[15]), "+f"(d[16]), "+f"(d[17]), "+f"(d[18]), "+f"(d[19]), "+f"(d[20]), "+f"(d[21]), "+f"(d[22]), "+f"(d[23]), "+f"(d[24]), "+f"(d[25]), "+f"(d[26]), "+f"(d[27]), "+f"(d[28]), "+f"(d[29]), "+f"(d[30]), "+f"(d[31])
    : "l"(a), "l"(ao), "l"(b), "l"(bo), "r"(sd), "n"(TA), "n"(TB));
}
template <int TA, int TB, int SZ>
__device__ __forceinline__ void wgmma_n96(float (&d)[SZ], uint64_t a, uint64_t ao, uint64_t b, uint64_t bo, int sd) {
  asm volatile("{ .reg .pred p; .reg .b64 da, db; setp.ne.b32 p, %52, 0; add.u64 da, %48, %49; add.u64 db, %50, %51;\n"
    "wgmma.mma_async.sync.aligned.m64n96k16.f32.bf16.bf16 {%0, %1, %2, %3, %4, %5, %6, %7, %8, %9, %10, %11, %12, %13, %14, %15, %16, %17, %18, %19, %20, %21, %22, %23, %24, %25, %26, %27, %28, %29, %30, %31, %32, %33, %34, %35, %36, %37, %38, %39, %40, %41, %42, %43, %44, %45, %46, %47}, da, db, p, 1, 1, %53, %54; }"
    : "+f"(d[0]), "+f"(d[1]), "+f"(d[2]), "+f"(d[3]), "+f"(d[4]), "+f"(d[5]), "+f"(d[6]), "+f"(d[7]), "+f"(d[8]), "+f"(d[9]), "+f"(d[10]), "+f"(d[11]), "+f"(d[12]), "+f"(d[13]), "+f"(d[14]), "+f"(d[15]), "+f"(d[16]), "+f"(d[17]), "+f"(d[18]), "+f"(d[19]), "+f"(d[20]), "+f"(d[21]), "+f"(d[22]), "+f"(d[23]), "+f"(d[24]), "+f"(d[25]), "+f"(d[26]), "+f"(d[27]), "+f"(d[28]), "+f"(d[29]), "+f"(d[30]), "+f"(d[31]), "+f"(d[32]), "+f"(d[33]), "+f"(d[34]), "+f"(d[35]), "+f"(d[36]), "+f"(d[37]), "+f"(d[38]), "+f"(d[39]), "+f"(d[40]), "+f"(d[41]), "+f"(d[42]), "+f"(d[43]), "+f"(d[44]), "+f"(d[45]), "+f"(d[46]), "+f"(d[47])
    : "l"(a), "l"(ao), "l"(b), "l"(bo), "r"(sd), "n"(TA), "n"(TB));
}
template <int TA, int TB, int SZ>
__device__ __forceinline__ void wgmma_n128(float (&d)[SZ], uint64_t a, uint64_t ao, uint64_t b, uint64_t bo, int sd) {
  asm volatile("{ .reg .pred p; .reg .b64 da, db; setp.ne.b32 p, %68, 0; add.u64 da, %64, %65; add.u64 db, %66, %67;\n"
    "wgmma.mma_async.sync.aligned.m64n128k16.f32.bf16.bf16 {%0, %1, %2, %3, %4, %5, %6, %7, %8, %9, %10, %11, %12, %13, %14, %15, %16, %17, %18, %19, %20, %21, %22, %23, %24, %25, %26, %27, %28, %29, %30, %31, %32, %33, %34, %35, %36, %37, %38, %39, %40, %41, %42, %43, %44, %45, %46, %47, %48, %49, %50, %51, %52, %53, %54, %55, %56, %57, %58, %59, %60, %61, %62, %63}, da, db, p, 1, 1, %69, %70; }"
    : "+f"(d[0]), "+f"(d[1]), "+f"(d[2]), "+f"(d[3]), "+f"(d[4]), "+f"(d[5]), "+f"(d[6]), "+f"(d[7]), "+f"(d[8]), "+f"(d[9]), "+f"(d[10]), "+f"(d[11]), "+f"(d[12]), "+f"(d[13]), "+f"(d[14]), "+f"(d[15]), "+f"(d[16]), "+f"(d[17]), "+f"(d[18]), "+f"(d[19]), "+f"(d[20]), "+f"(d[21]), "+f"(d[22]), "+f"(d[23]), "+f"(d[24]), "+f"(d[25]), "+f"(d[26]), "+f"(d[27]), "+f"(d[28]), "+f"(d[29]), "+f"(d[30]), "+f"(d[31]), "+f"(d[32]), "+f"(d[33]), "+f"(d[34]), "+f"(d[35]), "+f"(d[36]), "+f"(d[37]), "+f"(d[38]), "+f"(d[39]), "+f"(d[40]), "+f"(d[41]), "+f"(d[42]), "+f"(d[43]), "+f"(d[44]), "+f"(d[45]), "+f"(d[46]), "+f"(d[47]), "+f"(d[48]), "+f"(d[49]), "+f"(d[50]), "+f"(d[51]), "+f"(d[52]), "+f"(d[53]), "+f"(d[54]), "+f"(d[55]), "+f"(d[56]), "+f"(d[57]), "+f"(d[58]), "+f"(d[59]), "+f"(d[60]), "+f"(d[61]), "+f"(d[62]), "+f"(d[63])
    : "l"(a), "l"(ao), "l"(b), "l"(bo), "r"(sd), "n"(TA), "n"(TB));
}
template <int TB = 0>
__device__ __forceinline__ void wgmma_rs_n32(float (&d)[64], const uint32_t* a, uint64_t b, uint64_t bo, int sd) {
  asm volatile("{ .reg .pred p; .reg .b64 db; setp.ne.b32 p, %22, 0; add.u64 db, %20, %21;\n"
    "wgmma.mma_async.sync.aligned.m64n32k16.f32.bf16.bf16 {%0, %1, %2, %3, %4, %5, %6, %7, %8, %9, %10, %11, %12, %13, %14, %15}, {%16, %17, %18, %19}, db, p, 1, 1, %23; }"
    : "+f"(d[48]), "+f"(d[49]), "+f"(d[50]), "+f"(d[51]), "+f"(d[52]), "+f"(d[53]), "+f"(d[54]), "+f"(d[55]), "+f"(d[56]), "+f"(d[57]), "+f"(d[58]), "+f"(d[59]), "+f"(d[60]), "+f"(d[61]), "+f"(d[62]), "+f"(d[63])
    : "r"(a[0]), "r"(a[1]), "r"(a[2]), "r"(a[3]), "l"(b), "l"(bo), "r"(sd), "n"(TB));
}
template <int TB = 0>
__device__ __forceinline__ void wgmma_rs_n64(float (&d)[64], const uint32_t* a, uint64_t b, uint64_t bo, int sd) {
  asm volatile("{ .reg .pred p; .reg .b64 db; setp.ne.b32 p, %38, 0; add.u64 db, %36, %37;\n"
    "wgmma.mma_async.sync.aligned.m64n64k16.f32.bf16.bf16 {%0, %1, %2, %3, %4, %5, %6, %7, %8, %9, %10, %11, %12, %13, %14, %15, %16, %17, %18, %19, %20, %21, %22, %23, %24, %25, %26, %27, %28, %29, %30, %31}, {%32, %33, %34, %35}, db, p, 1, 1, %39; }"
    : "+f"(d[32]), "+f"(d[33]), "+f"(d[34]), "+f"(d[35]), "+f"(d[36]), "+f"(d[37]), "+f"(d[38]), "+f"(d[39]), "+f"(d[40]), "+f"(d[41]), "+f"(d[42]), "+f"(d[43]), "+f"(d[44]), "+f"(d[45]), "+f"(d[46]), "+f"(d[47]), "+f"(d[48]), "+f"(d[49]), "+f"(d[50]), "+f"(d[51]), "+f"(d[52]), "+f"(d[53]), "+f"(d[54]), "+f"(d[55]), "+f"(d[56]), "+f"(d[57]), "+f"(d[58]), "+f"(d[59]), "+f"(d[60]), "+f"(d[61]), "+f"(d[62]), "+f"(d[63])
    : "r"(a[0]), "r"(a[1]), "r"(a[2]), "r"(a[3]), "l"(b), "l"(bo), "r"(sd), "n"(TB));
}
template <int TB = 0>
__device__ __forceinline__ void wgmma_rs_n96(float (&d)[64], const uint32_t* a, uint64_t b, uint64_t bo, int sd) {
  asm volatile("{ .reg .pred p; .reg .b64 db; setp.ne.b32 p, %54, 0; add.u64 db, %52, %53;\n"
    "wgmma.mma_async.sync.aligned.m64n96k16.f32.bf16.bf16 {%0, %1, %2, %3, %4, %5, %6, %7, %8, %9, %10, %11, %12, %13, %14, %15, %16, %17, %18, %19, %20, %21, %22, %23, %24, %25, %26, %27, %28, %29, %30, %31, %32, %33, %34, %35, %36, %37, %38, %39, %40, %41, %42, %43, %44, %45, %46, %47}, {%48, %49, %50, %51}, db, p, 1, 1, %55; }"
    : "+f"(d[16]), "+f"(d[17]), "+f"(d[18]), "+f"(d[19]), "+f"(d[20]), "+f"(d[21]), "+f"(d[22]), "+f"(d[23]), "+f"(d[24]), "+f"(d[25]), "+f"(d[26]), "+f"(d[27]), "+f"(d[28]), "+f"(d[29]), "+f"(d[30]), "+f"(d[31]), "+f"(d[32]), "+f"(d[33]), "+f"(d[34]), "+f"(d[35]), "+f"(d[36]), "+f"(d[37]), "+f"(d[38]), "+f"(d[39]), "+f"(d[40]), "+f"(d[41]), "+f"(d[42]), "+f"(d[43]), "+f"(d[44]), "+f"(d[45]), "+f"(d[46]), "+f"(d[47]), "+f"(d[48]), "+f"(d[49]), "+f"(d[50]), "+f"(d[51]), "+f"(d[52]), "+f"(d[53]), "+f"(d[54]), "+f"(d[55]), "+f"(d[56]), "+f"(d[57]), "+f"(d[58]), "+f"(d[59]), "+f"(d[60]), "+f"(d[61]), "+f"(d[62]), "+f"(d[63])
    : "r"(a[0]), "r"(a[1]), "r"(a[2]), "r"(a[3]), "l"(b), "l"(bo), "r"(sd), "n"(TB));
}
template <int TB = 0>
__device__ __forceinline__ void wgmma_rs_n128(float (&d)[64], const uint32_t* a, uint64_t b, uint64_t bo, int sd) {
  asm volatile("{ .reg .pred p; .reg .b64 db; setp.ne.b32 p, %70, 0; add.u64 db, %68, %69;\n"
    "wgmma.mma_async.sync.aligned.m64n128k16.f32.bf16.bf16 {%0, %1, %2, %3, %4, %5, %6, %7, %8, %9, %10, %11, %12, %13, %14, %15, %16, %17, %18, %19, %20, %21, %22, %23, %24, %25, %26, %27, %28, %29, %30, %31, %32, %33, %34, %35, %36, %37, %38, %39, %40, %41, %42, %43, %44, %45, %46, %47, %48, %49, %50, %51, %52, %53, %54, %55, %56, %57, %58, %59, %60, %61, %62, %63}, {%64, %65, %66, %67}, db, p, 1, 1, %71; }"
    : "+f"(d[0]), "+f"(d[1]), "+f"(d[2]), "+f"(d[3]), "+f"(d[4]), "+f"(d[5]), "+f"(d[6]), "+f"(d[7]), "+f"(d[8]), "+f"(d[9]), "+f"(d[10]), "+f"(d[11]), "+f"(d[12]), "+f"(d[13]), "+f"(d[14]), "+f"(d[15]), "+f"(d[16]), "+f"(d[17]), "+f"(d[18]), "+f"(d[19]), "+f"(d[20]), "+f"(d[21]), "+f"(d[22]), "+f"(d[23]), "+f"(d[24]), "+f"(d[25]), "+f"(d[26]), "+f"(d[27]), "+f"(d[28]), "+f"(d[29]), "+f"(d[30]), "+f"(d[31]), "+f"(d[32]), "+f"(d[33]), "+f"(d[34]), "+f"(d[35]), "+f"(d[36]), "+f"(d[37]), "+f"(d[38]), "+f"(d[39]), "+f"(d[40]), "+f"(d[41]), "+f"(d[42]), "+f"(d[43]), "+f"(d[44]), "+f"(d[45]), "+f"(d[46]), "+f"(d[47]), "+f"(d[48]), "+f"(d[49]), "+f"(d[50]), "+f"(d[51]), "+f"(d[52]), "+f"(d[53]), "+f"(d[54]), "+f"(d[55]), "+f"(d[56]), "+f"(d[57]), "+f"(d[58]), "+f"(d[59]), "+f"(d[60]), "+f"(d[61]), "+f"(d[62]), "+f"(d[63])
    : "r"(a[0]), "r"(a[1]), "r"(a[2]), "r"(a[3]), "l"(b), "l"(bo), "r"(sd), "n"(TB));
}

__device__ __forceinline__ void st_either(int loc, uint32_t a, uint32_t x, uint32_t y, uint32_t z, uint32_t w, uint32_t bar) {
  if (loc == 1) asm volatile("st.shared.v4.b32 [%0], {%1,%2,%3,%4};" :: "r"(a), "r"(x), "r"(y), "r"(z), "r"(w) : "memory");
  if (loc == 0) st_async4(a, x, y, z, w, bar);
}
__device__ __forceinline__ void prep_task(int loc, uint32_t src, uint32_t dst, uint32_t bar, uint32_t w0, uint32_t w1, uint32_t w2, uint32_t w3) {
  uint32_t k[12], u[9];
#pragma unroll
  for (int j = 0; j < 12; j++) k[j] = lds32(j < 4 ? src + (4 + j) * 528 - 16 : src + (j - 4) * 528);
#pragma unroll
  for (int j = 0; j < 9; j++) u[j] = lds32(j < 1 ? src + 4224 + 7 * 528 - 16 : src + 4224 + (j - 1) * 528);
#pragma unroll
  for (int j = 0; j < 9; j++) {
    uint32_t s = bmul(k[j], w3);
    s = bfma(k[j + 1], w2, s); s = bfma(k[j + 2], w1, s); s = bfma(k[j + 3], w0, s);
    u[j] = bmul(s, u[j]);
  }
#pragma unroll
  for (int c = 0; c < 2; c++) {
    const uint32_t sel = c ? 0x7632 : 0x5410;
    st_either(loc, dst + c * U_PITCH, __byte_perm(u[2], u[1], sel), __byte_perm(u[4], u[3], sel), __byte_perm(u[6], u[5], sel), __byte_perm(u[8], u[7], sel), bar);
    st_either(loc, dst + c * U_PITCH + U_ODD, __byte_perm(u[1], u[0], sel), __byte_perm(u[3], u[2], sel), __byte_perm(u[5], u[4], sel), __byte_perm(u[7], u[6], sel), bar);
  }
}

template <int S, int C0, int NK>
__device__ __forceinline__ void frag_load(uint32_t (&P)[4 * NK], uint32_t ua, uint32_t z) {
  P[2] = lds32(ua + 1024 * S + 32 * C0 - 16);
#pragma unroll
  for (int kk = 0; kk < NK; kk++) { P[4 * kk] = lds32(ua + 1024 * S + 32 * (C0 + kk)); P[4 * kk + 1] = lds32(ua + 1024 * S + 32 * (C0 + kk) + 16); }
#pragma unroll
  for (int kk = 0; kk < NK; kk++) { P[4 * kk + 3] = P[4 * kk] ^ z; if (kk) P[4 * kk + 2] = P[4 * kk - 3] ^ z; }
#pragma unroll
  for (int i = 0; i < 4 * NK; i++) asm volatile("" : "+r"(P[i]) :: "memory");
}
template <int S, int C0, int NK, int CH>
__device__ __forceinline__ void conv_issue(float (&acc)[64], const uint32_t (&P)[4 * NK], uint64_t& db, uint64_t z64) {
  if (S > 0 && C0 == 0) reg_rename<16 * S, 64>(acc);
  if (C0 == 0 && CH == 0) db = fresh(db, z64);
  wg_fence();
#pragma unroll
  for (int kk = 0; kk < NK; kk++) {
    const uint64_t o = 16 - 2 * (C0 + kk) + CH * (T_PITCH / 8);
    if (S == 0) wgmma_rs_n128<0>(acc, &P[4 * kk], db, o, C0 + kk != 0);
    if (S == 1) wgmma_rs_n96<0>(acc, &P[4 * kk], db, o, 1);
    if (S == 2) wgmma_rs_n64<0>(acc, &P[4 * kk], db, o, 1);
    if (S == 3) wgmma_rs_n32<0>(acc, &P[4 * kk], db, o, 1);
  }
  wg_commit();
}
template <int S>
__device__ __forceinline__ void conv_dump(float (&acc)[64], uint32_t xw, int wl) {
  reg_fence<16 * S, 16 * S + 16>(acc);
#pragma unroll
  for (int r = 0; r < 3; r++) {
    const int i = 16 * S + 4 * (r + 1);
    if (S < 3 || wl + r + 1 < 4) sts64(xw + (4 * S + r + 1) * 768 + r * 256, pack2(acc[i], acc[i + 1]), pack2(acc[i + 2], acc[i + 3]));
  }
}
template <int S>
__device__ __forceinline__ void conv_reduce(float (&y)[4], const float (&acc)[64], uint32_t xw, int wl) {
#pragma unroll
  for (int i = 0; i < 4; i++) y[i] = acc[16 * S + i];
  uint2 v[3];
#pragma unroll
  for (int r = 0; r < 3; r++) {
    v[r] = make_uint2(0u, 0u);
    if (S > 0 || r < wl) v[r] = lds64(xw + 4 * S * 768 + r * 256);
  }
#pragma unroll
  for (int r = 0; r < 3; r++) {
    if (r < RED_H2) { v[r + 1].x = badd(v[r].x, v[r + 1].x); v[r + 1].y = badd(v[r].y, v[r + 1].y); }
    else { y[0] += blo(v[r].x); y[1] += bhi(v[r].x); y[2] += blo(v[r].y); y[3] += bhi(v[r].y); }
  }
}
struct FinCtx { uint32_t um, xt, st, DA, DB; uint32_t *hA, *hB; };
template <int S>
__device__ __forceinline__ void conv_z(uint32_t (&zz)[4], const FinCtx& c, const float (&aA)[64], const float (&aB)[64], uint32_t xA, uint32_t xB, int wl) {
  uint32_t u[4];
  float ya[4], yb[4];
  ldsm4t(c.um + S * 1024, u[0], u[1], u[2], u[3]);
  conv_reduce<S>(ya, aA, xA, wl); conv_reduce<S>(yb, aB, xB, wl);
  zz[0] = bfma(u[0], c.DA, pack2(ya[0], ya[1])); zz[1] = bfma(u[1], c.DA, pack2(ya[2], ya[3]));
  zz[2] = bfma(u[2], c.DB, pack2(yb[0], yb[1])); zz[3] = bfma(u[3], c.DB, pack2(yb[2], yb[3]));
}
template <int S>
__device__ __forceinline__ void conv_fin(const FinCtx& c, const uint32_t (&zz)[4]) {
  constexpr uint32_t XO = (S < 2 ? OFF_XTE : OFF_XTL) + (S & 1) * 4096, SO = (S < 2 ? OFF_STE : OFF_STL) + (S & 1) * 2048;
#pragma unroll
  for (int h = 0; h < 2; h++) {
    uint2 sv = lds64(c.st + SO + h * 256);
    uint32_t xa = lds32(c.xt + XO + h * 512), xb = lds32((c.xt ^ 64) + XO + h * 512);
    c.hA[(8 * S + h) * (D_ * 32)] = bfma(bfma(xa, sv.x, sv.y), zz[h], xa);
    c.hB[(8 * S + h) * (D_ * 32)] = bfma(bfma(xb, sv.x, sv.y), zz[2 + h], xb);
  }
}

struct RowC { float nm, k1, k2, hs; };
__device__ __forceinline__ float geglu(float g, float u, float cg, float cu, const RowC& r) {
  if (WHATIF & 1) return g * u;
  float gc = fmaf(r.nm, cg, g), uc = fmaf(r.nm, cu, u);
  if (WHATIF & (32 | 128)) { gc = g; uc = u; }
  if (WHATIF & 256) { gc = fmaf(r.nm, r.k1, g); uc = fmaf(r.nm, r.k2, u); }
  if (WHATIF & 512) { gc = g + r.nm; uc = u + r.nm; }
  float in = gc * fmaf(gc * gc, r.k2, r.k1);
  float t; asm("tanh.approx.f32 %0, %1;" : "=f"(t) : "f"(in));
  float pr = gc * uc;
  return fmaf(pr, t, pr);
}
template <int GI, int UI, int N>
__device__ __forceinline__ void epi_group(const float (&acc)[N], const float4& c, const RowC& r0, const RowC& r1, uint32_t* dst, uint32_t* keep = nullptr) {
  uint32_t lo = pack2(geglu(acc[GI], acc[UI], c.x, c.z, r0), geglu(acc[GI + 1], acc[UI + 1], c.y, c.w, r0));
  uint32_t hi = pack2(geglu(acc[GI + 2], acc[UI + 2], c.x, c.z, r1), geglu(acc[GI + 3], acc[UI + 3], c.y, c.w, r1));
  if (WHATIF & 128) { lo ^= (__float_as_uint(c.x) & __float_as_uint(c.y)) >> 31; hi ^= (__float_as_uint(c.z) & __float_as_uint(c.w)) >> 31; }
  dst[0] = lo; dst[32] = hi;
  if (keep) { keep[0] = lo; keep[1] = hi; }
}

__device__ __forceinline__ void mma_ones(float (&d)[4], uint32_t a0, uint32_t a1, uint32_t a2, uint32_t a3) {
  asm volatile("mma.sync.aligned.m16n8k16.row.col.f32.bf16.bf16.f32 {%0,%1,%2,%3}, {%4,%5,%6,%7}, {%8,%8}, {%0,%1,%2,%3};"
    : "+f"(d[0]), "+f"(d[1]), "+f"(d[2]), "+f"(d[3]) : "r"(a0), "r"(a1), "r"(a2), "r"(a3), "r"(0x3f803f80));
}

struct Params {
  const uint16_t *x, *shift_k, *ssm_k, *ssm_D, *wg, *wu, *wd;
  uint16_t* out;
  Scratch* scr;
  uint8_t map[NCTA];
  uint64_t z64;
};

__global__ void __launch_bounds__(NTHR, 1)
fused_kernel(const __grid_constant__ Params p, const __grid_constant__ CUtensorMap tmXR, const __grid_constant__ CUtensorMap tmT, const __grid_constant__ CUtensorMap tmK, const __grid_constant__ CUtensorMap tmV,
             const __grid_constant__ CUtensorMap tmG, const __grid_constant__ CUtensorMap tmU,
             const __grid_constant__ CUtensorMap tmG32, const __grid_constant__ CUtensorMap tmU32,
             const __grid_constant__ CUtensorMap tmD, const __grid_constant__ CUtensorMap tmX) {
  extern __shared__ __align__(1024) uint8_t smem[];
  const uint32_t sb = s2u(smem);
  const int xb = blockIdx.x;
  auto x_load = [&]() {
    const uint32_t b = sb + OFF_BAR + B_XR * 8;
    mbar_expect(b, 16384);
    asm volatile("cp.async.bulk.tensor.4d.shared::cluster.global.mbarrier::complete_tx::bytes [%0], [%1, {%3, %4, %5, %3}], [%2];"
                 :: "r"(sb + OFF_XR), "l"(&tmXR), "r"(b), "r"(0), "r"((xb & 7) * 2), "r"(xb & ~7) : "memory");
  };

  const int rank = blockIdx.x & 1;
  auto BAR = [&](int i) { return sb + OFF_BAR + i * 8; };
  auto kv_load = [&](int pc, int pr) {
    uint32_t b = BAR(B_KV + pc), d = sb + OFF_KV + pc * KV_PIECE;
    int run0 = pc * 64 + rank * 32 - 1;
    mbar_expect(b, KV_PIECE);
    tma3d(d, &tmK, pr * 8, run0, 0, b);
    tma3d(d + 4224, &tmV, pr * 8, run0, 0, b);
  };
  if (threadIdx.x < 32) {
    if (elect()) {
      mbar_init(BAR(B_XR), 1); mbar_init(BAR(B_SK), 1); mbar_init(BAR(B_KV), 1); mbar_init(BAR(B_TAP), 1); mbar_init(BAR(B_TAP + 1), 1);
      x_load();
      const int cl = blockIdx.x >> 1, q7 = ((cl - 36) * 37) >> 8;
      const int pr = cl < 4 ? cl : cl < 36 ? 4 + ((cl - 4) & 7) * 4 + ((cl - 4) >> 3) : 4 * cl - 108 - 27 * q7;
      mbar_expect(BAR(B_SK), 80);
      bulk_ld(sb + OFF_SK, p.shift_k + pr * 32, 64, BAR(B_SK));
      bulk_ld(sb + OFF_SK + 64, p.ssm_D + pr * 8, 16, BAR(B_SK));
      kv_load(0, pr);
#pragma unroll
      for (int i = 0; i < 2; i++) {
        mbar_expect(BAR(B_TAP + i), 2 * T_PITCH);
        tma3d(sb + OFF_TAP + i * 2 * T_PITCH, &tmT, 0, -1, pr * 8 + rank * 4 + 2 * i, BAR(B_TAP + i));
      }
      SSTAMP(true, 26);
    }
    __syncwarp();
  }
  const int bid = p.map[blockIdx.x], pair = bid >> 1;
  const int tile = bid >> 3, js = bid & 7;
  const int tid = (threadIdx.x + 384) & 511, lane = tid & 31;
  const int warp = __shfl_sync(0xffffffffu, tid >> 5, 0);
  const int g = lane >> 2, q = lane & 3;
  if (warp >= 8) {
    if (warp != 12 && elect()) {
      const int cnt = warp < 10 ? 8 : (warp < 12 ? 4 : 1), cnt0 = warp == 13 ? 5 : cnt;
#pragma unroll
      for (int i = 0; i < 10; i++) mbar_init(BAR((warp - 8) * 10 + i), i < 4 ? cnt0 : (warp == 9 || (i >= 6 && warp == 11) ? 1 : cnt));
      asm volatile("fence.mbarrier_init.release.cluster;" ::: "memory");
      if (warp == 14) {
#pragma unroll
        for (int i = 0; i < 3; i++) { mbar_init(BAR(B_KV + 1 + i), 1); mbar_init(BAR(B_CS + i), 1); }
      }
      if (warp == 13) {
#pragma unroll
        for (int i = 0; i < 8; i++) mbar_expect(BAR(B_U + i), i < 4 ? 4096 : i < 6 ? 8192 : 512);
      }
    }
    __syncwarp();
  } else {
    if (tid < 64) sts32(sb + OFF_U + (tid >> 4) * U_PITCH + ((tid >> 3) & 1) * U_ODD + (tid & 7) * 4, 0u);
  }
  __syncthreads();
  asm volatile("barrier.cluster.arrive.relaxed.aligned;" ::: "memory");
  SSTAMP(tid == 0, 13);

  auto pub_cs = [&]() {
    mbar_wait_bounded(BAR(B_CSD), 0);
    if (bid < 86) {
      const int which = bid >= 43, f = (bid - which * 43) * 32 + lane;
      const uint32_t a = sb + OFF_CS + lane * 4;
      const float sum = __uint_as_float(lds32(a)) + __uint_as_float(lds32(a + 128)) + __uint_as_float(lds32(a + 256)) + __uint_as_float(lds32(a + 384));
      const uint32_t lo = __shfl_up_sync(0xffffffffu, pack2(sum, 0.f), 1), sb_ = __float_as_uint(sum);
      const uint32_t hi = (sb_ & 0x7fffffffu) < 0x10000u ? sb_ : sb_ - lo + 0x8000u;
      if (lane & 1) p.scr->cs[(f >> 4) * 16 + ((f >> 1) & 3) * 4 + ((f >> 3) & 1) * 2 + which] = (hi & 0xffff0000u) | lo;
      __syncwarp();
    }
    if (lane == 0) signal_gpu(&p.scr->cnt[CNT_C * 32]);
    __syncwarp();
    STAMP_IF(lane == 0, 29);
  };
  if (warp < 8) {
    asm volatile("setmaxnreg.inc.sync.aligned.u32 %0;" :: "n"(REG_C));
    asm volatile("barrier.cluster.wait.aligned;" ::: "memory");
    uint2 small = make_uint2(0u, 0u);
#pragma unroll 1
    for (int pass = X_DRY ? 0 : 1; pass < 2; pass++) {
      if (pass) mbar_wait(BAR(B_XR), 0);
      SSTAMP(tid == 0, 49);
      const int mi = lane >> 3, rho = lane & 7;
      const int t = (rho & 1) + 4 * (rho >> 1) + 2 * (mi & 1);
      const int xrow = 2 * (t & 7) + ((t >> 3) ^ 1);
      const uint32_t xa = sb + OFF_XR + warp * 2048 + xrow * 128 + (((mi >> 1) ^ (xrow & 7)) * 16);
      const uint32_t xo = sb + OFF_XST + warp * 2048 + (g ^ (xb & 3)) * 32 + q * 8;
#pragma unroll
      for (int i = 0; i < 4; i++) {
        uint32_t m0, m1, m2, m3;
        ldsm4t(xa ^ (i * 32), m0, m1, m2, m3);
        sts64(xo + i * 512, m0, m1);
        sts64(xo + i * 512 + 256, m2, m3);
      }
      if (X_SPLIT) { __syncwarp(); if (lane == 0 && pass) mbar_arrive(BAR(B_SIGT)); }
      const int r = tid >> 4;
      const uint32_t ra = sb + OFF_XR + (2 * (r & 7) + ((r >> 3) ^ 1)) * 128 + (mi & 1) * 2048 + rho * 16;
      float f[32];
#pragma unroll
      for (int i = 0; i < 4; i++) {
        uint4 v = lds128(ra + i * 4096);
        f[8 * i] = blo(v.x); f[8 * i + 1] = bhi(v.x); f[8 * i + 2] = blo(v.y); f[8 * i + 3] = bhi(v.y);
        f[8 * i + 4] = blo(v.z); f[8 * i + 5] = bhi(v.z); f[8 * i + 6] = blo(v.w); f[8 * i + 7] = bhi(v.w);
      }
      const float c0 = blo(lds32(sb + OFF_XR + (2 * (r & 7) + ((r >> 3) ^ 1)) * 128));
      float sa = 0.f, sc = 0.f, qa = 0.f, qc = 0.f;
#pragma unroll
      for (int i = 0; i < 16; i++) { float d0 = f[2 * i] - c0, d1 = f[2 * i + 1] - c0; sa += d0; sc += d1; qa = fmaf(d0, d0, qa); qc = fmaf(d1, d1, qc); }
      sa += sc; qa += qc;
#pragma unroll
      for (int o = 1; o < 16; o <<= 1) { sa += __shfl_xor_sync(0xffffffffu, sa, o); qa += __shfl_xor_sync(0xffffffffu, qa, o); }
      const float md = sa * (1.f / D_), mean = md + c0;
      const float rs = blo(pack2(rsqrtf(fmaxf(fmaf(-md, md, qa * (1.f / D_)), 0.f) + 1e-5f), 0.f));
      const uint32_t me = pack2(rs, -mean * rs), ot = __shfl_xor_sync(0xffffffffu, me, 16);
      if (lane == 0) sts64(sb + OFF_CS + warp * 8, __byte_perm(me, ot, 0x5410), __byte_perm(me, ot, 0x7632));
      __syncwarp();
      if (lane == 0 && pass) mbar_arrive(BAR(B_SIGX));
      if (pass) { float w0;
        asm volatile("{ .reg .f32 a, b, c; mma.sync.aligned.m16n8k8.row.col.f32.bf16.bf16.f32 {%0,a,b,c}, {%1,%1}, {%1}, {%2,%2,%2,%2}; }"
                     : "=f"(w0) : "r"(blockIdx.x >> 16), "f"(0.f));
        small.x ^= __float_as_uint(w0); }
      SSTAMP(tid == 0, 48);
    }
    const int hw = warp >> 2, wl = warp & 3;
    {
      const int chA = bid * 4 + hw, chB = chA + 2;
      const int ig = g ^ 1;
      const uint32_t uA = sb + OFF_U + hw * U_PITCH + ((ig & 1) ? 0 : U_ODD) + 32 + ((ig - 2 * q) >> 1) * 4 + wl * 256;
      const uint32_t uB = uA + 2 * U_PITCH;
      uint64_t dT = mkdesc(sb + OFF_TAP + hw * T_PITCH, 16, 256, 3);
      const uint32_t z = blockIdx.x >> 16;
      const uint32_t xA = sb + OFF_XCH + (hw * 32 + wl) * 768 + lane * 8, xB = xA + 16 * 768;
      FinCtx fc;
      fc.um = sb + OFF_U + (hw + 2 * (lane >> 4)) * U_PITCH + 32 + wl * 256 + (lane & 7) * 32 + ((lane >> 3) & 1) * 16;
      fc.xt = sb + wl * 1024 + (lane >> 3) * 128 + (hw ^ (lane >> 3)) * 32 + (lane & 7) * 4;
      fc.st = sb + wl * 512 + lane * 8;
      mbar_wait(BAR(B_SK), 0);
      { const uint2 d4 = lds64(sb + OFF_SK + 64 + rank * 8); small.x ^= d4.x; small.y = d4.y; }
      fc.DA = __byte_perm(small.x, 0, hw ? 0x3232 : 0x1010); fc.DB = __byte_perm(small.y, 0, hw ? 0x3232 : 0x1010);
      fc.hA = (uint32_t*)p.scr->hT + (size_t)wl * 2 * (D_ * 32) + chA * 32 + ((g ^ (chA & 7)) * 4) + q;
      fc.hB = (uint32_t*)p.scr->hT + (size_t)wl * 2 * (D_ * 32) + chB * 32 + ((g ^ (chB & 7)) * 4) + q;
      auto tap_fix = [&](int i) {
        const uint32_t a = sb + OFF_TAP + (hw + 2 * i) * T_PITCH + 256 + ((tid & 127) >> 3) * 256 + 128 + (tid & 7) * 16;
        mbar_wait(BAR(B_TAP + i), 0);
        const uint4 v = lds128(a);
        __syncwarp();
        asm volatile("st.shared.v4.b32 [%0], {%1,%2,%3,%4};" :: "r"(a ^ 16), "r"(v.x), "r"(v.y), "r"(v.z), "r"(v.w) : "memory");
        fence_async_s();
        bar_sync(1 + hw, 128);
      };
      tap_fix(0);
      SSTAMP(tid == 0, 2);
      float aA[64], aB[64];
      uint32_t z0[4], z1[4];
      {
        uint32_t P[16], Q[16];
        mbar_wait_cluster(BAR(B_U + 0), 0);
        SSTAMP(tid == 0, 3);
        frag_load<0, 0, 4>(P, uA, z); conv_issue<0, 0, 4, 0>(aA, P, dT, p.z64);
        frag_load<0, 4, 4>(Q, uA, z); conv_issue<0, 4, 4, 0>(aA, Q, dT, p.z64);
        tap_fix(1);
        wg_wait<1>(); frag_load<0, 0, 4>(P, uB, z); conv_issue<0, 0, 4, 1>(aB, P, dT, p.z64);
        wg_wait<1>(); frag_load<0, 4, 4>(Q, uB, z); conv_issue<0, 4, 4, 1>(aB, Q, dT, p.z64);
        conv_dump<0>(aA, xA, wl);
        SSTAMP(tid == 0, 4);
        if (!(WHATIF & 16384)) mbar_wait_cluster(BAR(B_U + 1), 0);
        SSTAMP(tid == 0, 5);
        wg_wait<1>(); frag_load<1, 0, 4>(P, uA, z); conv_issue<1, 0, 4, 0>(aA, P, dT, p.z64);
        wg_wait<1>(); frag_load<1, 4, 4>(Q, uA, z); conv_issue<1, 4, 4, 0>(aA, Q, dT, p.z64);
        conv_dump<0>(aB, xB, wl);
        wg_wait<1>(); frag_load<1, 0, 4>(P, uB, z); conv_issue<1, 0, 4, 1>(aB, P, dT, p.z64);
        bar_sync(1 + hw, 128);
        conv_z<0>(z0, fc, aA, aB, xA, xB, wl);
        wg_wait<1>(); frag_load<1, 4, 4>(Q, uB, z); conv_issue<1, 4, 4, 1>(aB, Q, dT, p.z64);
        conv_dump<1>(aA, xA, wl);
      }
      {
        uint32_t P[32], Q[32], R[32];
        SSTAMP(tid == 0, 6);
        if (!(WHATIF & 16384)) mbar_wait_cluster(BAR(B_U + 2), 0);
        wg_wait<1>(); frag_load<2, 0, 8>(P, uA, z); conv_issue<2, 0, 8, 0>(aA, P, dT, p.z64);
        frag_load<2, 0, 8>(Q, uB, z); wg_wait<1>(); conv_issue<2, 0, 8, 1>(aB, Q, dT, p.z64);
        conv_dump<1>(aB, xB, wl);
        bar_sync(1 + hw, 128);
        conv_z<1>(z1, fc, aA, aB, xA, xB, wl);
        SSTAMP(tid == 0, 1);
        if (CONV_ORDER != 4 && !(WHATIF & 8192)) mbar_wait(BAR(B_XT), 0);
        SSTAMP(tid == 0, 7);
        if (CONV_ORDER != 4) conv_fin<0>(fc, z0);
        conv_fin<1>(fc, z1);
        __syncwarp();
        if (lane == 0) mbar_arrive(BAR(B_SIGE + 0));
        SSTAMP(tid == 0, 8);
        mbar_wait_cluster(BAR(B_U + 3), 0);
        frag_load<3, 0, 8>(R, uA, z); wg_wait<1>(); conv_issue<3, 0, 8, 0>(aA, R, dT, p.z64);
        frag_load<3, 0, 8>(P, uB, z); wg_wait<1>(); conv_issue<3, 0, 8, 1>(aB, P, dT, p.z64);
        SSTAMP(tid == 0, 9);
        conv_dump<2>(aA, xA, wl); conv_dump<2>(aB, xB, wl);
        wg_wait<0>();
        conv_dump<3>(aA, xA, wl); conv_dump<3>(aB, xB, wl);
        SSTAMP(tid == 0, 10);
        bar_sync(1 + hw, 128);
        mbar_wait(BAR(B_XT + 1), 0);
        SSTAMP(tid == 0, 11);
        conv_z<2>(z0, fc, aA, aB, xA, xB, wl);
        conv_fin<2>(fc, z0);
        conv_z<3>(z1, fc, aA, aB, xA, xB, wl);
        conv_fin<3>(fc, z1);
        __syncwarp();
        if (lane == 0) mbar_arrive(BAR(B_SIGE + 1));
        STAMP_IF(tid == 0, 12);
      }
    }
    const int blk = tile + 16 * hw;
    const uint32_t aw = sb + OFF_A + hw * 65536;
    const uint32_t fullA = BAR(B_FULLA + hw * 8), emptyA = BAR(B_EMPTYA + hw * 6);
    const uint32_t lmo = aw + (((lane >> 4) * 8 + (lane & 7)) * 128) + (((2 * wl + ((lane >> 3) & 1)) ^ (lane & 7)) * 16);
    uint64_t da = fresh(mkdesc(aw - 16, 0, 1024, 1), p.z64), db = fresh(mkdesc(sb + OFF_RING - 16, 8192, 1024, 1), p.z64);
    float acc1[64], acc2[64];
    RowC r0, r1;
    const int TS = 16 + hw * 16; (void)TS;

    const uint32_t csa = sb + OFF_CS + q * 16;
    float4 cc[22];
    auto ldcs = [&](int i0, int i1) {
#pragma unroll
      for (int i = i0; i < i1; i += 2) {
        const uint4 v = lds128(csa + i * 32);
        cc[i] = make_float4(blo(v.x), __uint_as_float(v.x), blo(v.y), __uint_as_float(v.y));
        cc[i + 1] = make_float4(blo(v.z), __uint_as_float(v.z), blo(v.w), __uint_as_float(v.w));
      }
    };
    uint32_t res[16], own1[16], own2[16];
    auto ldres = [&]() {
#pragma unroll
      for (int kk = 0; kk < 4; kk++) ldsm4t(lmo + js * 8192 + kk * 2048, res[4 * kk], res[4 * kk + 1], res[4 * kk + 2], res[4 * kk + 3]);
    };
#pragma unroll
    for (int s = 0; s < 8; s++) {
      mbar_wait(fullA + s * 8, 0);
      STAMP_IF(wl == 0 && lane == 0 && s == 0, TS + 0);
      mbar_wait(BAR(B_FULLR + s % 6), s >= 6);
      wg_fence();
#pragma unroll
      for (int kk = 0; kk < 4; kk++) wgmma_n128<1, 1>(acc1, da, 1 + s * 512 + kk * 128, db, 1 + (s % 6) * 1024 + kk * 128, (s | kk) != 0);
      wg_commit();
      if (s == 3) db = fresh(db, p.z64);
      if (s > 0) { wg_wait<1>(); if (lane == 0) mbar_arrive(BAR(B_EMPTYR + (s - 1) % 6)); }
    }
    STAMP_IF(wl == 0 && lane == 0, TS + 1);
    uint32_t* hdst = (uint32_t*)p.scr->H + (size_t)blk * (86 * 512) + wl * 64 + lane;
    da = fresh(da, p.z64); db = fresh(db, p.z64);
#pragma unroll
    for (int s = 0; s < 8; s++) {
      constexpr int R0 = 8;
      const int r = R0 + s, slot = r % 6;
      mbar_wait(BAR(B_FULLR + slot), (r / 6) & 1);
      wg_fence();
#pragma unroll
      for (int kk = 0; kk < 4; kk++) wgmma_n128<1, 1>(acc2, da, 1 + s * 512 + kk * 128, db, 1 + slot * 1024 + kk * 128, (s | kk) != 0);
      if (s == 3) db = fresh(db, p.z64);
      wg_commit();
      uint32_t* d = hdst + js * 8 * 256;
      if (s == STX_AT) {
        if (!(WHATIF & 4096)) mbar_wait_cluster(BAR(B_STX + hw), 0);
        auto mk = [](uint2 v) {
          const float rs = __uint_as_float(v.y), r2 = rs * rs;
          RowC r; r.nm = __uint_as_float(v.x); r.k1 = 0.7978845608028654f * rs; r.k2 = 0.044715f * r2 * r.k1; r.hs = 0.5f * r2;
          return r;
        };
        r0 = mk(lds64(sb + OFF_STX + warp * 128 + g * 8)); r1 = mk(lds64(sb + OFF_STX + warp * 128 + 64 + g * 8));
      }
      if (s == 0 && !(WHATIF & 2048)) mbar_wait(BAR(B_CS), 0);
      if (s == 1) reg_fence<0, 64>(acc1);
      static_for<0, 8>([&](auto ic) {
        constexpr int i = decltype(ic)::v;
        if (s == ((EPI1 >> (4 * i)) & 15)) epi_group<4 * i, 32 + 4 * i>(acc1, cc[i], r0, r1, d + i * 256, &own1[2 * i]);
      });
      if (s == (EPI1 >> 28)) { __syncwarp(); if (lane == 0) mbar_arrive(BAR(B_SIGH + 0)); }
      static_for<0, 4>([&](auto ic) {
        constexpr int i = decltype(ic)::v;
        if (s + 1 == ((EPI1 >> (8 * i)) & 15)) ldcs(2 * i, 2 * i + 2);
      });
      if (s == RES_AT) ldres();
      if (s >= 6) ldcs(8 + 4 * (s - 6), 12 + 4 * (s - 6));
      wg_wait<1>();
      if (lane == 0) mbar_arrive(BAR(B_EMPTYR + (r - 1) % 6));
    }
    STAMP_IF(wl == 0 && lane == 0, TS + 2);
    da = fresh(da, p.z64); db = fresh(mkdesc(sb + OFF_RING - 16, 4096, 512, 2), p.z64);
    float acc3[48];
#pragma unroll
    for (int s = 0; s < 8; s++) {
      constexpr int R0 = 16;
      const int r = R0 + s, slot = r % 6;
      mbar_wait(BAR(B_FULLR + slot), (r / 6) & 1);
      wg_fence();
#pragma unroll
      for (int kk = 0; kk < 4; kk++) wgmma_n96<1, 1>(acc3, da, 1 + s * 512 + kk * 128, db, 1 + slot * 1024 + kk * 64, (s | kk) != 0);
      if (s == 3) db = fresh(db, p.z64);
      wg_commit();
      uint32_t* d = hdst + (64 + js * 8) * 256;
      if (s == 0) {
        wg_wait<1>();
        if (lane == 0) mbar_arrive(BAR(B_EMPTYR + (r - 1) % 6));
        reg_fence<0, 64>(acc2);
      }
      static_for<0, 8>([&](auto ic) {
        constexpr int i = decltype(ic)::v;
        if (s == ((EPI2 >> (4 * i)) & 15)) epi_group<4 * i, 32 + 4 * i>(acc2, cc[8 + i], r0, r1, d + i * 256, &own2[2 * i]);
      });
      if (s == (EPI2 >> 28)) { __syncwarp(); if (lane == 0) mbar_arrive(BAR(B_SIGH + 1)); }
      if (s >= CS3_AT && s < CS3_AT + 3) ldcs(16 + 2 * (s - CS3_AT), 18 + 2 * (s - CS3_AT));
      if (s > 0) {
        wg_wait<1>();
        if (lane == 0) { mbar_arrive(BAR(B_EMPTYR + (r - 1) % 6)); if (s < 7) mbar_arrive(emptyA + (s - 1) * 8); }
      }
    }
    STAMP_IF(wl == 0 && lane == 0, TS + 3);
    da = fresh(mkdesc(aw - 16, 1024, 128, 0), p.z64); db = fresh(mkdesc(sb + OFF_RING - 16, 8192, 1024, 1), p.z64);
    float acco[64], base[32];
    {
      mbar_wait(BAR(B_FULLR), 0);
      wg_fence();
#pragma unroll
      for (int kk = 0; kk < 4; kk++) wgmma_rs_n128<1>(acco, &own1[4 * kk], db, 1 + kk * 128, kk != 0);
      wg_commit();
      wg_wait<1>();
      if (lane == 0) {
        mbar_arrive(BAR(B_EMPTYR + 23 % 6));
        asm volatile("mbarrier.arrive.relaxed.cluster.shared::cluster.b64 _, [%0];" :: "r"(mapa(BAR(B_PEER + hw), rank ^ 1)) : "memory");
      }
      reg_fence<0, 48>(acc3);
      uint32_t* d = hdst + (128 + js * 4) * 256;
      uint32_t* dx = hdst + (160 + js * 2) * 256;
      epi_group<0, 16>(acc3, cc[16], r0, r1, d); epi_group<4, 20>(acc3, cc[17], r0, r1, d + 256);
      auto e3b = [&]() { epi_group<8, 24>(acc3, cc[18], r0, r1, d + 512); epi_group<12, 28>(acc3, cc[19], r0, r1, d + 768); };
      auto e3c = [&]() {
        if (js < 6) { epi_group<32, 40>(acc3, cc[20], r0, r1, dx); epi_group<36, 44>(acc3, cc[21], r0, r1, dx + 256); }
        __syncwarp();
        if (lane == 0) mbar_arrive(BAR(B_SIGH + 2));
        STAMP_IF(wl == 0 && lane == 0, TS + 4);
      };
      if (EPI3B == 0) e3b();
      if (EPI3C == 0) e3c();
#pragma unroll
      for (int s = 1; s < 8; s++) {
        const int slot = s % 6, ps = (s - 1) % 6, hsl = s - 1 - (s > 4), hp = s - 2 - (s > 5);
        if (s != 4) mbar_wait(fullA + hsl * 8, 1);
        mbar_wait(BAR(B_FULLR + slot), s >= 6);
        wg_fence();
#pragma unroll
        for (int kk = 0; kk < 4; kk++) {
          if (s == 4) wgmma_rs_n128<1>(acco, &own2[4 * kk], db, 1 + slot * 1024 + kk * 128, 1);
          else wgmma_n128<0, 1>(acco, da, 1 + hsl * 512 + kk * 128, db, 1 + slot * 1024 + kk * 128, 1);
        }
        wg_commit();
        if (s == EPI3B) e3b();
        if (s == EPI3C) e3c();
        if (s == 3) {
          da = fresh(da, p.z64); db = fresh(db, p.z64);
#pragma unroll
          for (int i = 0; i < 16; i++) { base[2 * i] = blo(res[i]); base[2 * i + 1] = bhi(res[i]); }
          reg_fence<0, 32>(base);
        }
        wg_wait<1>();
        if (lane == 0) { if (s != 1 && s != 5) mbar_arrive(emptyA + hp * 8); if (s < 6) mbar_arrive(BAR(B_EMPTYR + ps)); }
        STAMP_IF(wl == 0 && lane == 0 && s == 4, TS + 5);
      }
    }
    da = fresh(da, p.z64); db = fresh(db, p.z64);
    const uint32_t ob = aw + 6 * 8192 + wl * 2048;
    uint32_t oa;
    { const int orow = 2 * (lane & 7) + (((lane >> 3) & 1) ^ 1); oa = ob + orow * 128 + (((lane >> 4) ^ (orow & 7)) * 16); }
    uint32_t ol = ob + (lane >> 3) * 128 + (((lane & 7) ^ (lane >> 3)) * 16);
    uint16_t* og = p.out + (size_t)((blk >> 1) * 128 + (blk & 1) * 8 + wl * 2 + (lane >> 4) * 16 + ((lane >> 3) & 1)) * D_ + js * 64 + (lane & 7) * 8;
    float accn[32];
    {
      const uint32_t ra = mapa(ob + lane * 16, rank ^ 1), rb = mapa(BAR(B_RECV + hw), rank ^ 1);
      auto send = [&]() {
        reg_fence<0, 64>(acco);
        STAMP_IF(wl == 0 && lane == 0, TS + 6);
#pragma unroll
        for (int i = 0; i < 4; i++)
          st_async4(ra + i * 512, pack2(acco[32 + 8 * i], acco[33 + 8 * i]), pack2(acco[34 + 8 * i], acco[35 + 8 * i]),
                    pack2(acco[36 + 8 * i], acco[37 + 8 * i]), pack2(acco[38 + 8 * i], acco[39 + 8 * i]), rb);
      };
      mbar_wait_cluster(BAR(B_PEER + hw), 0);
      if (SEND_AT == 7) { wg_wait<0>(); send(); }
#pragma unroll
      for (int s = 8; s < 14; s++) {
        const int slot = h_slot(s - 2), rs = 2 + ((s - 8) >> 1);
        mbar_wait(fullA + slot * 8, h_par(s - 2));
        if ((s & 1) == 0) mbar_wait(BAR(B_FULLR + rs), 1);
        STAMP_IF(wl == 0 && lane == 0 && s == 8, TS + 7);
        wg_fence();
#pragma unroll
        for (int kk = 0; kk < (s == 13 ? 2 : 4); kk++)
          wgmma_n64<0, 1>(accn, da, 1 + slot * 512 + kk * 128, db, 2049 + (s - 8) * 512 + kk * 128, s > 8 || kk > 0);
        wg_commit();
        if (s == SEND_AT) { wg_wait<(SEND_AT > 7 ? SEND_AT - 7 : 0)>(); send(); }
        if (s == OWN_AT) {
#pragma unroll
          for (int i = 0; i < 32; i++) base[i] = fmaf(acco[i], (i & 2) ? r1.hs : r0.hs, base[i]);
          reg_fence<0, 32>(base);
        }
        if (s == BASE_AT) {
          mbar_wait_cluster(BAR(B_RECV + hw), 0);
          if (lane == 0) mbar_arrive(BAR(B_SIG + 6));
          STAMP_IF(tid == 0, 0);
#pragma unroll
          for (int i = 0; i < 4; i++) {
            const uint4 o = lds128(ob + lane * 16 + i * 512);
            const uint32_t ov[4] = {o.x, o.y, o.z, o.w};
#pragma unroll
            for (int j = 0; j < 4; j++) {
              const float hs = (j & 1) ? r1.hs : r0.hs;
              base[8 * i + 2 * j] = fmaf(blo(ov[j]), hs, base[8 * i + 2 * j]); base[8 * i + 2 * j + 1] = fmaf(bhi(ov[j]), hs, base[8 * i + 2 * j + 1]);
            }
          }
          reg_fence<0, 32>(base);
        }
      }
    }
    {
      wg_wait<0>();
      reg_fence<0, 32>(accn);
      STAMP_IF(wl == 0 && lane == 0, TS + 8);
#pragma unroll
      for (int i = 0; i < 32; i++) acco[i] = fmaf(accn[i], (i & 2) ? r1.hs : r0.hs, base[i]);
      __syncwarp();
#pragma unroll
      for (int i = 0; i < 4; i++)
        stsm4(oa ^ (i * 32), pack2(acco[8 * i], acco[8 * i + 1]), pack2(acco[8 * i + 2], acco[8 * i + 3]),
              pack2(acco[8 * i + 4], acco[8 * i + 5]), pack2(acco[8 * i + 6], acco[8 * i + 7]));
      __syncwarp();
#pragma unroll
      for (int i = 0; i < 4; i++) *(uint4*)(og + (size_t)i * 32 * D_) = lds128((ol + i * 512) ^ ((i & 1) * 64));
    }
    STAMP_IF(wl == 0 && lane == 0, TS + 9);
    STAMP_NS(tid == 0, 15);
  } else if (warp < 12) {
    asm volatile("setmaxnreg.dec.sync.aligned.u32 %0;" :: "n"(REG_P));
    const int h = warp - 8;
    uint32_t w0 = 0, w1 = 0, w2 = 0, w3 = 0;
    const uint32_t psrc = sb + OFF_KV + 16 + lane * 4 + h * 128;
    const uint32_t pdst = mapa(sb + OFF_U + (q & 1) * 2 * U_PITCH + 32 + rank * 512 + g * 16 + h * 128, q >> 1), pbar = mapa(BAR(B_U), q >> 1);
    asm volatile("barrier.cluster.wait.aligned;" ::: "memory");
#pragma unroll 1
    for (int pc = -P_DRY; pc < 4; pc++) {
      if (pc == 0) {
        mbar_wait(BAR(B_SK), 0);
        const uint4 sk = lds128(sb + OFF_SK + q * 16);
        w0 = __byte_perm(sk.x, sk.z, 0x5410); w1 = __byte_perm(sk.x, sk.z, 0x7632);
        w2 = __byte_perm(sk.y, sk.w, 0x5410); w3 = __byte_perm(sk.y, sk.w, 0x7632);
      }
      if (pc >= 0) mbar_wait(BAR(B_KV + pc), 0);
      SSTAMP(h == 0 && lane == 0 && pc >= 0, 42 + pc);
      prep_task(pc < 0 ? 2 : (q >> 1) == rank, psrc + pc * KV_PIECE, pdst + pc * 1024, pbar + pc * 8, w0, w1, w2, w3);
      __syncwarp();
      if (lane == 0 && pc >= 0) mbar_arrive(BAR(B_U + pc));
      SSTAMP(h == 0 && lane == 0 && pc == 0, 27);
    }
    __syncwarp();
    if (lane == 0) mbar_arrive(BAR(B_PREPD));
    SSTAMP(h == 0 && lane == 0, 51);
    if (bid < NCS) {
      mbar_wait(BAR(B_CW), 0);
      if (CS_EVT >= 0) mbar_wait(BAR(B_SIGE + CS_EVT), 0);
      if (bid < 86) {
        const uint32_t wa = sb + OFF_CW + h * 8192 + ((lane >> 4) * 8 + (lane & 7)) * 64 + ((((lane >> 3) & 1) ^ ((lane & 7) >> 1)) * 16);
        float d0[4] = {0.f, 0.f, 0.f, 0.f}, d1[4] = {0.f, 0.f, 0.f, 0.f};
#pragma unroll 2
        for (int j = 0; j < 8; j++) {
          uint32_t a0, a1, a2, a3;
          ldsm4t(wa + j * 1024, a0, a1, a2, a3); mma_ones(d0, a0, a1, a2, a3);
          ldsm4t((wa ^ 32) + j * 1024, a0, a1, a2, a3); mma_ones(d1, a0, a1, a2, a3);
        }
        sts32(sb + OFF_CS + h * 128 + (q * 8 + g) * 4, __float_as_uint(q & 2 ? (q & 1 ? d1[2] : d1[0]) : (q & 1 ? d0[2] : d0[0])));
      } else {
        const int t = bid - 86, which = t >= 12, uu = (t - which * 12) >> 2, k0 = (t & 3) * 128 + h * 32 + g;
        uint16_t* d = p.scr->wX + (size_t)(uu * 2 + (q >> 1)) * (D_ * 32) + k0 * 32 + ((which * 2 + (q & 1)) ^ (g >> 1)) * 8;
#pragma unroll
        for (int i = 0; i < 4; i++) *(uint4*)(d + i * 256) = lds128(sb + OFF_CW + h * 2048 + g * 64 + ((q ^ (g >> 1)) * 16) + i * 512);
      }
      STAMP_IF(h == 0 && lane == 0, 53);
    }
    __syncwarp();
    if (lane == 0) mbar_arrive(BAR(B_CSD));
    const int ck = rank * 4 + h;
    const uint32_t sdst = mapa(sb + OFF_STX + (ck * 8 + g) * 8, q & 1), sbar = mapa(BAR(B_STX), q & 1);
#pragma unroll 1
    for (int w = 0; w < 2; w++) {
      uint32_t la = sb + OFF_A + w * 65536 + lane * 128 + ((ck ^ (lane & 7)) * 16);
      float s0 = 0.f, s1 = 0.f, q0 = 0.f, q1 = 0.f, c = 0.f;
#pragma unroll 1
      for (int s = 0; s < 8; s++) {
        uint32_t m[8];
        mbar_wait(BAR(B_FULLA + w * 8 + s), 0);
        ldsm4t(la, m[0], m[1], m[2], m[3]); ldsm4t(la + 4096, m[4], m[5], m[6], m[7]);
        la += 8192;
        if (STAT_SHIFT && s == 0) c = __shfl_sync(0xffffffffu, blo(m[0]), lane & ~3);
#pragma unroll
        for (int i = 0; i < 8; i++) {
          float d0 = blo(m[i]), d1 = bhi(m[i]);
          if (STAT_SHIFT) { d0 -= c; d1 -= c; }
          if ((WHATIF & 1024) && i >= 2) continue;
          s0 += d0; s1 += d1; q0 = fmaf(d0, d0, q0); q1 = fmaf(d1, d1, q1);
        }
      }
      s0 += s1; q0 += q1;
#pragma unroll
      for (int o = 1; o < 4; o <<= 1) { s0 += __shfl_xor_sync(0xffffffffu, s0, o); q0 += __shfl_xor_sync(0xffffffffu, q0, o); }
      const float md = s0 * (1.f / D_), var = fmaxf(fmaf(-md, md, q0 * (1.f / D_)), 0.f);
      if (q < 2) asm volatile("st.async.weak.shared::cluster.mbarrier::complete_tx::bytes.v2.f32 [%0], {%1,%2}, [%3];"
                              :: "r"(sdst + w * 512), "f"(-(md + c)), "f"(rsqrtf(var + 1e-5f)), "r"(sbar + w * 8) : "memory");
      STAMP_IF(h == 0 && lane == 0, 46 + w);
    }
  } else {
    asm volatile("setmaxnreg.dec.sync.aligned.u32 %0;" :: "n"(512 - 2 * REG_C - REG_P));
    const int h = warp - 12;
    asm volatile("barrier.cluster.wait.aligned;" ::: "memory");
    if (h == 0) {
      if (elect()) {
#pragma unroll
        for (int pc = 1; pc < 4; pc++) {
          if (pc == KV_HOLD) mbar_wait(BAR(B_GO), 0);
          if (pc == 1 && KV_EVT) mbar_wait(BAR(B_XR), 0);
          if (pc == XS_BEFORE) mbar_wait(BAR(B_XSI), 0);
          if (pc == 3 && KV3_EVT == 1) mbar_wait(BAR(B_KV + 1), 0);
          if (pc == 3 && KV3_EVT == 2) mbar_wait(BAR(B_KV + 2), 0);
          if (pc == 2 && KV_EVT == 1) mbar_wait(BAR(B_KV), 0);
          if (pc == 2 && KV_EVT == 2) mbar_wait(BAR(B_TAP), 0);
          if (pc == 2 && KV_EVT == 3) mbar_wait(BAR(B_U), 0);
          kv_load(pc, pair);
          if (pc == PF_W) {
            asm volatile("cp.async.bulk.prefetch.L2.global [%0], %1;" :: "l"((const char*)p.wg + (size_t)bid * 11008), "r"(11008) : "memory");
            asm volatile("cp.async.bulk.prefetch.L2.global [%0], %1;" :: "l"((const char*)p.wu + (size_t)bid * 11008), "r"(11008) : "memory");
          }
        }
        const int cw = js * 64, c3 = 1024 + js * 32, co = cw ^ 64, b3 = js < 6 ? 12288 : 8192;
        const uint16_t* wx = p.scr->wX + (size_t)js * (D_ * 32);
        if (PRE_EVT != 2) mbar_wait(BAR(B_GO), 0);
        if (PF_W == 4) {
          asm volatile("cp.async.bulk.prefetch.L2.global [%0], %1;" :: "l"((const char*)p.wg + (size_t)bid * 11008), "r"(11008) : "memory");
          asm volatile("cp.async.bulk.prefetch.L2.global [%0], %1;" :: "l"((const char*)p.wu + (size_t)bid * 11008), "r"(11008) : "memory");
        }
        if (PRE_EVT == 0) mbar_wait(BAR(B_KV + 3), 0);
        if (PRE_EVT == 2) mbar_wait(BAR(B_KV + 2), 0);
        if (PRE_EVT == 3) mbar_wait(BAR(B_XT), 0);
        const uint16_t* hs0 = p.scr->H + (size_t)tile * (86 * 1024);
        static_for<0, SCHED_N>([&](auto ic) {
          constexpr int it = decltype(ic)::v, r = SCHED[it];
          if constexpr (r == 2 && PRE_EVT == 2) mbar_wait(BAR(B_GO), 0);
          if constexpr (r == CW_AT) {
            if (bid < NCS) {
              mbar_wait(BAR(B_PREPD), 0);
              fence_async_s();
              const bool up = bid < 86 ? bid >= 43 : bid >= 98;
              const int nb = bid < 86 ? 8 : 2, t = bid - (up ? 98 : 86);
              const int col = (bid < 86 ? bid - (up ? 43 : 0) : 40 + (t >> 2)) * 32, k0 = bid < 86 ? 0 : (t & 3) * 128;
              mbar_expect(BAR(B_CW), nb * 4096);
#pragma unroll 1
              for (int i = 0; i < nb; i++) tma2d(sb + OFF_CW + i * 4096, up ? &tmU32 : &tmG32, col, k0 + i * 64, BAR(B_CW));
            }
            if (PF_W == 5) {
              asm volatile("cp.async.bulk.prefetch.L2.global [%0], %1;" :: "l"((const char*)p.wg + (size_t)bid * 11008), "r"(11008) : "memory");
              asm volatile("cp.async.bulk.prefetch.L2.global [%0], %1;" :: "l"((const char*)p.wu + (size_t)bid * 11008), "r"(11008) : "memory");
            }
            STAMP(28);
          }
          if constexpr (r == 3) {
            mbar_wait(BAR(R3_EVT ? B_SIGE + 1 : B_GO + 1), 0);
            fence_async_s();
            if (R_AFTER_A >= 0) mbar_wait(BAR(B_FULLA + R_AFTER_A), 0);
          }
          if constexpr (r == PF_D) asm volatile("cp.async.bulk.prefetch.L2.global [%0], %1;" :: "l"((const char*)p.wd + (size_t)bid * 11008), "r"(11008) : "memory");
          if constexpr (r == 16) mbar_wait(BAR(B_CS), 0);
          if constexpr (r == P1) mbar_wait(BAR(B_GOH + 1), 0);
          if constexpr (r == P2) mbar_wait(BAR(B_GOH + 2), 0);
          constexpr int w = r & 1, hs = (r - 64) >> 1;
          if constexpr (r >= 64) {
            if constexpr (w == 0 && hs % 3 == 0 && hs < 9) { mbar_wait(BAR(B_SEEN + hs / 3), 0); fence_async_g(); }
            if constexpr (hs != 9) mbar_wait(BAR(B_EMPTYA + w * 6 + h_slot(hs)), hs >= 6);
          } else if constexpr (r >= 6) mbar_wait(BAR(B_EMPTYR + r % 6), (r / 6 - 1) & 1);
          static_for<SchedDep<it - 1>::v + 1, SchedDep<it>::v + 1>([&](auto jc) {
            constexpr int j = decltype(jc)::v, o = SCHED[j], os = (o - 64) >> 1;
            if constexpr (!SchedReused<j, it>::v) {
              if constexpr (o < 64) mbar_wait(BAR(B_FULLR + o % 6), (o / 6) & 1);
              else mbar_wait(BAR(B_FULLA + (o & 1) * 8 + h_slot(os)), h_par(os));
            }
          });
          const uint32_t b = BAR(B_FULLR + r % 6), d = sb + OFF_RING + (r % 6) * 16384;
          if constexpr (r >= 64) {
            const uint32_t fb = BAR(B_FULLA + w * 8 + h_slot(hs));
            mbar_expect(fb, hs == 11 ? 4096 : 8192);
            bulk_ld(sb + OFF_A + w * 65536 + h_slot(hs) * 8192,
                    hs0 + (hs < 6 ? hs / 3 * 8 + ((js + 2 * (hs % 3) + 2) & 7) : hs + 10) * 4096 + (size_t)w * (16 * 86 * 1024), hs == 11 ? 4096 : 8192, fb);
          } else if constexpr (r < 16) {
            mbar_expect(b, 16384);
            tma2d(d, &tmG, cw + (r >> 3) * 512, (r & 7) * 64, b); tma2d(d + 8192, &tmU, cw + (r >> 3) * 512, (r & 7) * 64, b);
          } else if constexpr (r < 24) {
            mbar_expect(b, b3);
            tma2d(d, &tmG32, c3, (r & 7) * 64, b); tma2d(d + 4096, &tmU32, c3, (r & 7) * 64, b);
            if (js < 6) bulk_ld(d + 8192, wx + (r & 7) * 2048, 4096, b);
          } else if constexpr (r < 32) {
            const int k = ((r & 4) * 2 + ((js + 2 * (r & 3)) & 7)) * 64;
            mbar_expect(b, 16384);
            tma2d(d, &tmD, cw, k, b); tma2d(d + 8192, &tmD, co, k, b);
          } else {
            mbar_expect(b, 16384);
            tma2d(d, &tmD, cw, 1024 + (r - 32) * 128, b); tma2d(d + 8192, &tmD, cw, 1088 + (r - 32) * 128, b);
          }
        });
      }
    } else if (h == 3) {
      mbar_wait_bounded(BAR(X_SPLIT ? B_SIGT : B_SIGX), 0);
      fence_async_s();
      if (elect()) {
        asm volatile("cp.async.bulk.tensor.2d.global.shared::cta.bulk_group [%0, {%2, %3}], [%1];" :: "l"(&tmX), "r"(sb + OFF_XST), "r"(xb * 64), "r"(0) : "memory");
        mbar_arrive(BAR(B_XSI));
      }
      __syncwarp();
#pragma unroll 1
      for (int i = 0; i < 7; i++) {
        mbar_wait_bounded(BAR(B_SIG + i), 0);
        if (i == 6) break;
        if (SIG2 && i == 1) continue;
        unsigned* c = &p.scr->cnt[(i < 3 ? i : CNT_H + tile * 3 + i - 3) * 32];
        if (i == 0) {
          fence_async_s();
          if (elect()) {
            asm volatile("cp.async.bulk.global.shared::cta.bulk_group [%0], [%1], 64;" :: "l"(p.scr->st1 + xb * 16), "r"(sb + OFF_CS) : "memory");
            asm volatile("cp.async.bulk.commit_group;" ::: "memory");
            asm volatile("cp.async.bulk.wait_group 0;" ::: "memory");
          }
          __syncwarp();
        }
        if (lane == 0) { if (((WHATIF & 2) && i >= 3 && ((NOF >> (i - 3)) & 1)) || ((WHATIF & 16) && i > 0 && i < 3) || ((WHATIF & 64) && i == 0)) asm volatile("red.relaxed.gpu.global.add.u32 [%0], 1;" :: "l"(c) : "memory"); else signal_gpu(c); if (i == 0 || i == 2) mbar_arrive(BAR(B_GO + (i >> 1))); if (i >= 3) mbar_arrive(BAR(B_GOH + i - 3)); }
        __syncwarp();
        STAMP_IF(lane == 0, i == 0 ? 50 : 53 + i);
        if (!C_BY_PREP && i == 2 && bid < NCS) pub_cs();
      }
    } else {
      const unsigned ep = p.scr->epoch[blockIdx.x] + 1;
      const int w = h - 1, blk = tile + 16 * w;
      const uint32_t aw = sb + OFF_A + w * 65536;
      const uint32_t fullA = BAR(B_FULLA + w * 8);
      if (elect()) {
        if (w == 0) {
          mbar_wait(BAR(B_GO), 0);
          poll1(&p.scr->cnt[CNT_X * 32], ep * NCTA);
          fence_async_g(); fence_async_s();
          uint32_t b = BAR(B_XT);
          mbar_expect(b, 12288); mbar_expect(b + 8, 12288);
          bulk_ld(sb + OFF_XTE, p.scr->xT + (size_t)bid * 8192, 8192, b);
          bulk_ld(sb + OFF_STE, p.scr->st1, 4096, b);
          bulk_ld(sb + OFF_XTL, p.scr->xT + (size_t)bid * 8192 + 4096, 8192, b + 8);
          bulk_ld(sb + OFF_STL, p.scr->st1 + 1024, 4096, b + 8);
          SSTAMP(true, 52);
        }
      const uint16_t* asrc = p.scr->hT + (size_t)blk * (D_ * 64);
      const unsigned* hc = &p.scr->cnt[(CNT_H + tile * 3) * 32];
        if (SIG2 && w == 1) { mbar_wait(BAR(B_SIGE), 0); signal_gpu(&p.scr->cnt[CNT_E * 32]); STAMP(54); }
        mbar_wait(w ? BAR(B_GO + 1) : BAR(B_SIGE), 0);
        fence_async_s();
        if (!(WHATIF & 8)) poll1(&p.scr->cnt[(CNT_E + w) * 32], ep * NCTA);
        STAMP(59 + w);
        if (A_AFTER_GO) mbar_wait(BAR(B_GO + 1), 0);
        fence_async_g();
#pragma unroll
        for (int s = 0; s < 8; s++) {
          if (s == 3 && w == 0) { mbar_wait(BAR(B_CSD), 0); fence_async_s(); }
          if (s >= A_DEPTH0 && w == 0) mbar_wait(fullA + (s - A_DEPTH0) * 8, 0);
          if (s >= A_DEPTH && w == 1) mbar_wait(fullA + (s - A_DEPTH) * 8, 0);
          mbar_expect(fullA + s * 8, 8192);
          bulk_ld(aw + s * 8192, asrc + s * 4096, 8192, fullA + s * 8);
        }
        if (w == 0) {
          poll1(&p.scr->cnt[CNT_C * 32], ep * NCS);
          fence_async_g(); fence_async_s();
          uint32_t b = BAR(B_CS), d = sb + OFF_CS;
          mbar_expect(b, (js < 6 ? 704 : 640));
          bulk_ld(d, p.scr->cs + js * 64, 256, b);
          bulk_ld(d + 256, p.scr->cs + (512 + js * 64), 256, b);
          bulk_ld(d + 512, p.scr->cs + (1024 + js * 32), 128, b);
          if (js < 6) bulk_ld(d + 640, p.scr->cs + (1280 + js * 16), 64, b);
          STAMP(30);
        }
        if (w == 1) {
#pragma unroll 1
          for (int c = 0; c < 3; c++) {
            if (!(WHATIF & 4)) { mbar_wait(BAR(B_SIGH + c), 0);
            poll1(hc + c * 32, ep * 8); }
            mbar_arrive(BAR(B_SEEN + c));
            STAMP(61 + c);
          }
          p.scr->epoch[blockIdx.x] = ep;
        }
      }
    }
  }
}

typedef CUresult (*EncFn)(CUtensorMap*, CUtensorMapDataType, cuuint32_t, void*, const cuuint64_t*, const cuuint64_t*,
                          const cuuint32_t*, const cuuint32_t*, CUtensorMapInterleave, CUtensorMapSwizzle,
                          CUtensorMapL2promotion, CUtensorMapFloatOOBfill);

void make_map(EncFn fn, CUtensorMap* tm, const void* ptr, int w, int hgt, int bw, int bh, CUtensorMapSwizzle sw, CUtensorMapL2promotion pr) {
  cuuint64_t dims[2] = {(cuuint64_t)w, (cuuint64_t)hgt};
  cuuint64_t str[1] = {(cuuint64_t)w * 2};
  cuuint32_t box[2] = {(cuuint32_t)bw, (cuuint32_t)bh}, es[2] = {1, 1};
  fn(tm, CU_TENSOR_MAP_DATA_TYPE_BFLOAT16, 2, (void*)ptr, dims, str, box, es, CU_TENSOR_MAP_INTERLEAVE_NONE, sw, pr,
     CU_TENSOR_MAP_FLOAT_OOB_FILL_NONE);
}

void make_map_runs(EncFn fn, CUtensorMap* tm, const void* ptr) {
  cuuint64_t dims[3] = {(cuuint64_t)D_, (cuuint64_t)(S_ / 8), 8};
  cuuint64_t str[2] = {(cuuint64_t)D_ * 16, (cuuint64_t)D_ * 2};
  cuuint32_t box[3] = {8, 33, 8}, es[3] = {1, 1, 1};
  fn(tm, CU_TENSOR_MAP_DATA_TYPE_BFLOAT16, 3, (void*)ptr, dims, str, box, es, CU_TENSOR_MAP_INTERLEAVE_NONE,
     CU_TENSOR_MAP_SWIZZLE_NONE, CU_TENSOR_MAP_L2_PROMOTION_L2_128B, CU_TENSOR_MAP_FLOAT_OOB_FILL_NONE);
}

}

extern "C" void kernel_launch(void* const* d_in, const int* in_sizes, int n_in, void* d_out, int out_size) {
  (void)in_sizes; (void)n_in; (void)out_size;
  static EncFn fn = nullptr;
  if (!fn) {
    void* f = nullptr; cudaDriverEntryPointQueryResult qr;
    cudaGetDriverEntryPoint("cuTensorMapEncodeTiled", &f, cudaEnableDefault, &qr);
    fn = (EncFn)f;
    cudaFuncSetAttribute(fused_kernel, cudaFuncAttributeMaxDynamicSharedMemorySize, SMEM_BYTES);
  }
  CUtensorMap tmK, tmV, tmG, tmU, tmG32, tmU32, tmD, tmX, tmXR, tmT;
  void* xT = nullptr;
  cudaGetSymbolAddress(&xT, g_scr);
  make_map(fn, &tmX, xT, 8192, 128, 64, 128, CU_TENSOR_MAP_SWIZZLE_NONE, CU_TENSOR_MAP_L2_PROMOTION_NONE);
  {
    cuuint64_t dims[3] = {128, 16, (cuuint64_t)D_}, str[2] = {256, (cuuint64_t)S_ * 2};
    cuuint32_t box[3] = {128, 17, 2}, es[4] = {1, 1, 1, 1};
    fn(&tmT, CU_TENSOR_MAP_DATA_TYPE_BFLOAT16, 3, d_in[4], dims, str, box, es, CU_TENSOR_MAP_INTERLEAVE_NONE,
       CU_TENSOR_MAP_SWIZZLE_NONE, CU_TENSOR_MAP_L2_PROMOTION_NONE, CU_TENSOR_MAP_FLOAT_OOB_FILL_NONE);
    cuuint64_t dims4[4] = {64, 16, 128, 8}, str4[3] = {1024, 16384, 128};
    cuuint32_t box4[4] = {64, 2, 8, 8};
    fn(&tmXR, CU_TENSOR_MAP_DATA_TYPE_BFLOAT16, 4, d_in[0], dims4, str4, box4, es, CU_TENSOR_MAP_INTERLEAVE_NONE,
       CU_TENSOR_MAP_SWIZZLE_128B, (CUtensorMapL2promotion)PROMO_X, CU_TENSOR_MAP_FLOAT_OOB_FILL_NONE);
  }
  make_map_runs(fn, &tmK, d_in[1]);
  make_map_runs(fn, &tmV, d_in[2]);
  make_map(fn, &tmG, d_in[7], F_, D_, 64, 64, CU_TENSOR_MAP_SWIZZLE_128B, (CUtensorMapL2promotion)PROMO_W);
  make_map(fn, &tmU, d_in[8], F_, D_, 64, 64, CU_TENSOR_MAP_SWIZZLE_128B, (CUtensorMapL2promotion)PROMO_W);
  make_map(fn, &tmG32, d_in[7], F_, D_, 32, 64, CU_TENSOR_MAP_SWIZZLE_64B, (CUtensorMapL2promotion)PROMO_W32);
  make_map(fn, &tmU32, d_in[8], F_, D_, 32, 64, CU_TENSOR_MAP_SWIZZLE_64B, (CUtensorMapL2promotion)PROMO_W32);
  make_map(fn, &tmD, d_in[9], D_, F_, 64, 64, CU_TENSOR_MAP_SWIZZLE_128B, CU_TENSOR_MAP_L2_PROMOTION_NONE);
  Params p;
  p.x = (const uint16_t*)d_in[0]; p.shift_k = (const uint16_t*)d_in[3]; p.ssm_k = (const uint16_t*)d_in[4];
  p.ssm_D = (const uint16_t*)d_in[5]; p.wg = (const uint16_t*)d_in[7]; p.wu = (const uint16_t*)d_in[8];
  p.wd = (const uint16_t*)d_in[9]; p.out = (uint16_t*)d_out; p.scr = (Scratch*)xT; p.z64 = 0;
  for (int cl = 0; cl < NCTA / 2; cl++) {
    const int pr = cl < 4 ? cl : cl < 36 ? 4 + ((cl - 4) & 7) * 4 + ((cl - 4) >> 3) : 36 + ((cl - 36) % 7) * 4 + (cl - 36) / 7;
    p.map[2 * cl] = (uint8_t)(2 * pr); p.map[2 * cl + 1] = (uint8_t)(2 * pr + 1);
  }
  cudaLaunchConfig_t cfg = {};
  cfg.gridDim = dim3(NCTA); cfg.blockDim = dim3(NTHR); cfg.dynamicSmemBytes = SMEM_BYTES; cfg.stream = cudaStreamPerThread;
  cudaLaunchAttribute at[1];
  at[0].id = cudaLaunchAttributeClusterDimension; at[0].val.clusterDim.x = 2; at[0].val.clusterDim.y = 1; at[0].val.clusterDim.z = 1;
  cfg.attrs = at; cfg.numAttrs = 1;
  cudaLaunchKernelEx(&cfg, fused_kernel, p, tmXR, tmT, tmK, tmV, tmG, tmU, tmG32, tmU32, tmD, tmX);
}
```

```cpp
#include <cuda_runtime.h>
#include <cuda_bf16.h>
#include <cuda.h>
#include <stdint.h>

namespace {

constexpr int S_ = 2048, D_ = 512, F_ = 1376;
constexpr int NCTA = 128, NTHR = 512;
constexpr int NCS = 110;
constexpr int REG_C = 216, REG_P = 48, REG_M = 32;

struct __align__(1024) Scratch {
  uint16_t xT[D_ * S_];
  uint16_t hT[32 * D_ * 64];
  uint16_t H[32 * 86 * 1024];
  uint16_t wX[6 * D_ * 32];
  uint32_t st1[S_];
  uint32_t cs[F_];
  unsigned cnt[(4 + 32) * 32];
  unsigned epoch[NCTA];
};
__device__ Scratch g_scr;
constexpr int CNT_X = 0, CNT_E = 1, CNT_C = 3, CNT_H = 4;

constexpr uint32_t OFF_A    = 0;
constexpr uint32_t OFF_RING = 131072;
constexpr uint32_t OFF_CS   = 229376;
constexpr uint32_t OFF_SK   = OFF_CS + 1024;
constexpr uint32_t OFF_BAR  = OFF_CS + 1408;
constexpr uint32_t OFF_STX  = OFF_BAR + 640;
constexpr uint32_t SMEM_BYTES = 232448;
constexpr uint32_t KV_PIECE = 8448;
constexpr uint32_t OFF_KV   = 65536 - 4 * KV_PIECE;
constexpr uint32_t OFF_CW   = 32768;
constexpr uint32_t OFF_XR   = 0;
constexpr uint32_t OFF_XTE  = OFF_XR;
constexpr uint32_t OFF_STE  = OFF_XR + 8192;
constexpr uint32_t U_PITCH  = 8352, U_ODD = 4160;
constexpr uint32_t T_PITCH  = 4352;
constexpr uint32_t OFF_TAP  = 65536;
constexpr uint32_t OFF_U    = OFF_TAP + 4 * T_PITCH;
constexpr uint32_t OFF_XTL  = OFF_U + 4 * U_PITCH;
constexpr uint32_t OFF_STL  = OFF_XTL + 8192;
constexpr uint32_t OFF_XST  = OFF_RING + 2 * 16384;
constexpr uint32_t OFF_XCH  = OFF_RING + 3 * 16384;
static_assert(OFF_XR % 1024 == 0 && OFF_XR + 16384 <= 65536, "");
static_assert(OFF_STL + 4096 <= 131072, "");
static_assert(OFF_STX + 1024 <= SMEM_BYTES, "");
constexpr int B_EMPTYR = 0  , B_SIG = 6  ,
              B_EMPTYA = 20  , B_PEER = 32  , B_PREPD = 34, B_CSD = 35, B_SEENP = 36  ,
              B_KV = 40  , B_XR = 44, B_TAP = 45  , B_CS = 47, B_GO = 48  ,
              B_U = 50  , B_RECV = 54  , B_STX = 56  , B_XT = 58  , B_FULLA = 60  , B_CW = 76, B_SEEN = 77, B_GOH = 78,
              B_FULLR = 14  ;
constexpr int B_SK = -1, B_SIGX = B_SIG, B_SIGE = B_SIG + 1, B_SIGH = B_SIG + 3;

#define HH(s) 64 + 2 * (s), 65 + 2 * (s)
constexpr int SCHED_N = 35 + 22;
constexpr int SCHED[SCHED_N] = {0, 1, 2, 3, 4, 5, 6, 7, 8, 9, 10, 11, 12, 13, 14, 15, 16, 17, 18, 19, 20, 21,
  22, 23, 24, HH(0), 25, HH(1), 26, HH(2), 27, 28, 29, 30, 31, 32, HH(3), HH(4), 33, HH(5),
  HH(6), HH(7), 34, HH(8), HH(9), HH(10)};
__host__ __device__ constexpr int h_slot(int s) { return s < 6 ? s : s < 9 ? s - 6 : s == 9 ? 7 : s - 7; }
__host__ __device__ constexpr int h_par(int s) { return s < 6 || s == 9; }
constexpr int sched_kb(int v) { return v >= 64 ? 8 : v >= 16 && v < 24 ? 12 : 16; }
constexpr int sched_dep(int i) {
  int best = -1;
  for (int k = 0; k <= i; k++) {
    int acc = 0, win = k < 16 ? 32 : k < 39 ? 200 : 72;
    for (int j = k; j >= 0; j--) { acc += sched_kb(SCHED[j]); if (acc > win) { if (j > best) best = j; break; } }
  }
  return best;
}
constexpr bool sched_reused(int j, int i) {
  for (int k = j + 1; k <= i; k++) {
    const int a = SCHED[j], b = SCHED[k];
    if (a < 64 ? b == a + 6 : (b >= 64 && !((a ^ b) & 1) && h_slot((a - 64) >> 1) == h_slot((b - 64) >> 1))) return true;
  }
  return false;
}
template <int I> struct SchedDep { static constexpr int v = sched_dep(I); };
template <int J, int I> struct SchedReused { static constexpr bool v = sched_reused(J, I); };
template <int I> struct IC { static constexpr int v = I; };
template <int I, int E, class F> __device__ __forceinline__ void static_for(F&& f) { if constexpr (I < E) { f(IC<I>{}); static_for<I + 1, E>(f); } }

__device__ __forceinline__ uint32_t s2u(const void* p) { return (uint32_t)__cvta_generic_to_shared(p); }
__device__ __forceinline__ void mbar_init(uint32_t b, int n) { asm volatile("mbarrier.init.shared::cta.b64 [%0], %1;" :: "r"(b), "r"(n) : "memory"); }
__device__ __forceinline__ void mbar_expect(uint32_t b, int bytes) { asm volatile("mbarrier.arrive.expect_tx.shared::cta.b64 _, [%0], %1;" :: "r"(b), "r"(bytes) : "memory"); }
__device__ __forceinline__ void mbar_arrive(uint32_t b) { asm volatile("mbarrier.arrive.shared::cta.b64 _, [%0];" :: "r"(b) : "memory"); }
__device__ __forceinline__ void mbar_wait(uint32_t b, int par) {
  asm volatile("{\n .reg .pred p;\nSPIN:\n mbarrier.try_wait.parity.shared::cta.b64 p, [%0], %1;\n @!p bra SPIN;\n}" :: "r"(b), "r"(par) : "memory");
}
__device__ __forceinline__ void mbar_wait_cluster(uint32_t b, int par) {
  mbar_wait(b, par);
  asm volatile("fence.acquire.sync_restrict::shared::cluster.cluster;" ::: "memory");
}
__device__ __forceinline__ void mbar_wait_bounded(uint32_t b, int par) {
  asm volatile("{\n .reg .pred p, t; .reg .u32 c;\n mov.u32 c, 0;\n"
    "SPIN:\n mbarrier.try_wait.parity.shared::cta.b64 p, [%0], %1;\n @p bra DONE;\n"
    " add.u32 c, c, 1;\n setp.lt.u32 t, c, 1048576;\n @t bra SPIN;\n trap;\nDONE:\n}" :: "r"(b), "r"(par) : "memory");
}
__device__ __forceinline__ uint32_t mapa(uint32_t a, int r) { uint32_t d; asm("mapa.shared::cluster.u32 %0, %1, %2;" : "=r"(d) : "r"(a), "r"(r)); return d; }
__device__ __forceinline__ void st_async4(uint32_t a, uint32_t x, uint32_t y, uint32_t z, uint32_t w, uint32_t bar) {
  asm volatile("st.async.weak.shared::cluster.mbarrier::complete_tx::bytes.v4.b32 [%0], {%1,%2,%3,%4}, [%5];" :: "r"(a), "r"(x), "r"(y), "r"(z), "r"(w), "r"(bar) : "memory");
}
__device__ __forceinline__ void tma3d(uint32_t dst, const CUtensorMap* tm, int c0, int c1, int c2, uint32_t bar) {
  asm volatile("cp.async.bulk.tensor.3d.shared::cluster.global.mbarrier::complete_tx::bytes [%0], [%1, {%3, %4, %5}], [%2];" :: "r"(dst), "l"(tm), "r"(bar), "r"(c0), "r"(c1), "r"(c2) : "memory");
}
__device__ __forceinline__ void sts64(uint32_t a, uint32_t x, uint32_t y) { asm volatile("st.shared.v2.b32 [%0], {%1,%2};" :: "r"(a), "r"(x), "r"(y) : "memory"); }
__device__ __forceinline__ bool elect() { uint32_t p; asm volatile("{ .reg .pred P; elect.sync _|P, 0xffffffff; selp.u32 %0, 1, 0, P; }" : "=r"(p)); return p; }
__device__ __forceinline__ void bulk_ld(uint32_t dst, const void* src, int bytes, uint32_t bar) {
  asm volatile("cp.async.bulk.shared::cluster.global.mbarrier::complete_tx::bytes [%0], [%1], %2, [%3];" :: "r"(dst), "l"(src), "r"(bytes), "r"(bar) : "memory");
}
__device__ __forceinline__ void tma2d(uint32_t dst, const CUtensorMap* tm, int c0, int c1, uint32_t bar) {
  asm volatile("cp.async.bulk.tensor.2d.shared::cluster.global.mbarrier::complete_tx::bytes [%0], [%1, {%3, %4}], [%2];" :: "r"(dst), "l"(tm), "r"(bar), "r"(c0), "r"(c1) : "memory");
}
__device__ __forceinline__ void fence_async_g() { asm volatile("fence.proxy.async.global;" ::: "memory"); }
__device__ __forceinline__ void fence_async_s() { asm volatile("fence.proxy.async.shared::cta;" ::: "memory"); }
__device__ __forceinline__ void poll1(const unsigned* p, unsigned target) {
  unsigned v;
  do { asm volatile("ld.relaxed.gpu.global.u32 %0, [%1];" : "=r"(v) : "l"(p) : "memory"); } while ((int)(v - target) < 0);
  asm volatile("fence.acquire.gpu;" ::: "memory");
}
__device__ __forceinline__ void signal_gpu(unsigned* p) {
  asm volatile("fence.release.gpu;" ::: "memory");
  asm volatile("red.relaxed.gpu.global.add.u32 [%0], 1;" :: "l"(p) : "memory");
}
__device__ __forceinline__ void bar_sync(int id, int n) { asm volatile("bar.sync %0, %1;" :: "r"(id), "r"(n) : "memory"); }
__device__ __forceinline__ uint32_t lds32(uint32_t a) { uint32_t v; asm volatile("ld.shared.b32 %0, [%1];" : "=r"(v) : "r"(a)); return v; }
__device__ __forceinline__ uint2 lds64(uint32_t a) { uint2 v; asm volatile("ld.shared.v2.b32 {%0,%1}, [%2];" : "=r"(v.x), "=r"(v.y) : "r"(a)); return v; }
__device__ __forceinline__ uint4 lds128(uint32_t a) { uint4 v; asm volatile("ld.shared.v4.b32 {%0,%1,%2,%3}, [%4];" : "=r"(v.x), "=r"(v.y), "=r"(v.z), "=r"(v.w) : "r"(a)); return v; }
__device__ __forceinline__ void sts32(uint32_t a, uint32_t v) { asm volatile("st.shared.b32 [%0], %1;" :: "r"(a), "r"(v) : "memory"); }
__device__ __forceinline__ void ldsm4t(uint32_t a, uint32_t& r0, uint32_t& r1, uint32_t& r2, uint32_t& r3) {
  asm volatile("ldmatrix.sync.aligned.m8n8.x4.trans.shared.b16 {%0,%1,%2,%3}, [%4];" : "=r"(r0), "=r"(r1), "=r"(r2), "=r"(r3) : "r"(a));
}
__device__ __forceinline__ void stsm4(uint32_t a, uint32_t r0, uint32_t r1, uint32_t r2, uint32_t r3) {
  asm volatile("stmatrix.sync.aligned.m8n8.x4.shared.b16 [%0], {%1,%2,%3,%4};" :: "r"(a), "r"(r0), "r"(r1), "r"(r2), "r"(r3) : "memory");
}
__device__ __forceinline__ uint32_t bmul(uint32_t a, uint32_t b) { uint32_t d; asm("mul.rn.bf16x2 %0, %1, %2;" : "=r"(d) : "r"(a), "r"(b)); return d; }
__device__ __forceinline__ uint32_t bfma(uint32_t a, uint32_t b, uint32_t c) { uint32_t d; asm("fma.rn.bf16x2 %0, %1, %2, %3;" : "=r"(d) : "r"(a), "r"(b), "r"(c)); return d; }
__device__ __forceinline__ float blo(uint32_t v) { return __uint_as_float(v << 16); }
__device__ __forceinline__ float bhi(uint32_t v) { return __uint_as_float(v & 0xffff0000u); }
__device__ __forceinline__ uint32_t pack2(float lo, float hi) { uint32_t d; asm("cvt.rn.bf16x2.f32 %0, %1, %2;" : "=r"(d) : "f"(hi), "f"(lo)); return d; }
__device__ __forceinline__ uint64_t mkdesc(uint32_t addr, uint32_t lbo, uint32_t sbo, int swz) {
  return (uint64_t)((addr & 0x3FFFF) >> 4) | ((uint64_t)(lbo >> 4) << 16) | ((uint64_t)(sbo >> 4) << 32) | ((uint64_t)swz << 62);
}
__device__ __forceinline__ void wg_fence() { asm volatile("wgmma.fence.sync.aligned;" ::: "memory"); }
__device__ __forceinline__ void wg_commit() { asm volatile("wgmma.commit_group.sync.aligned;" ::: "memory"); }
template <int N> __device__ __forceinline__ void wg_wait() { asm volatile("wgmma.wait_group.sync.aligned %0;" :: "n"(N) : "memory"); }
template <int I0, int I1, int N> __device__ __forceinline__ void reg_fence(float (&d)[N]) {
#pragma unroll
  for (int i = I0; i < I1; i++) asm volatile("" : "+f"(d[i]) :: "memory");
}
template <int I0, int I1, int N> __device__ __forceinline__ void reg_rename(float (&d)[N]) {
#pragma unroll
  for (int i = I0; i < I1; i++) { float t; asm volatile("mov.b32 %0, %1;" : "=f"(t) : "f"(d[i]) : "memory"); d[i] = t; }
}
__device__ __forceinline__ uint64_t fresh(uint64_t d, uint64_t z) { asm volatile("add.u64 %0, %0, %1;" : "+l"(d) : "l"(z)); return d; }
template <int TA, int TB, int SZ>
__device__ __forceinline__ void wgmma_n64(float (&d)[SZ], uint64_t a, uint64_t ao, uint64_t b, uint64_t bo, int sd) {
  asm volatile("{ .reg .pred p; .reg .b64 da, db; setp.ne.b32 p, %36, 0; add.u64 da, %32, %33; add.u64 db, %34, %35;\n"
    "wgmma.mma_async.sync.aligned.m64n64k16.f32.bf16.bf16 {%0, %1, %2, %3, %4, %5, %6, %7, %8, %9, %10, %11, %12, %13, %14, %15, %16, %17, %18, %19, %20, %21, %22, %23, %24, %25, %26, %27, %28, %29, %30, %31}, da, db, p, 1, 1, %37, %38; }"
    : "+f"(d[0]), "+f"(d[1]), "+f"(d[2]), "+f"(d[3]), "+f"(d[4]), "+f"(d[5]), "+f"(d[6]), "+f"(d[7]), "+f"(d[8]), "+f"(d[9]), "+f"(d[10]), "+f"(d[11]), "+f"(d[12]), "+f"(d[13]), "+f"(d[14]), "+f"(d[15]), "+f"(d[16]), "+f"(d[17]), "+f"(d[18]), "+f"(d[19]), "+f"(d[20]), "+f"(d[21]), "+f"(d[22]), "+f"(d[23]), "+f"(d[24]), "+f"(d[25]), "+f"(d[26]), "+f"(d[27]), "+f"(d[28]), "+f"(d[29]), "+f"(d[30]), "+f"(d[31])
    : "l"(a), "l"(ao), "l"(b), "l"(bo), "r"(sd), "n"(TA), "n"(TB));
}
template <int TA, int TB, int SZ>
__device__ __forceinline__ void wgmma_n96(float (&d)[SZ], uint64_t a, uint64_t ao, uint64_t b, uint64_t bo, int sd) {
  asm volatile("{ .reg .pred p; .reg .b64 da, db; setp.ne.b32 p, %52, 0; add.u64 da, %48, %49; add.u64 db, %50, %51;\n"
    "wgmma.mma_async.sync.aligned.m64n96k16.f32.bf16.bf16 {%0, %1, %2, %3, %4, %5, %6, %7, %8, %9, %10, %11, %12, %13, %14, %15, %16, %17, %18, %19, %20, %21, %22, %23, %24, %25, %26, %27, %28, %29, %30, %31, %32, %33, %34, %35, %36, %37, %38, %39, %40, %41, %42, %43, %44, %45, %46, %47}, da, db, p, 1, 1, %53, %54; }"
    : "+f"(d[0]), "+f"(d[1]), "+f"(d[2]), "+f"(d[3]), "+f"(d[4]), "+f"(d[5]), "+f"(d[6]), "+f"(d[7]), "+f"(d[8]), "+f"(d[9]), "+f"(d[10]), "+f"(d[11]), "+f"(d[12]), "+f"(d[13]), "+f"(d[14]), "+f"(d[15]), "+f"(d[16]), "+f"(d[17]), "+f"(d[18]), "+f"(d[19]), "+f"(d[20]), "+f"(d[21]), "+f"(d[22]), "+f"(d[23]), "+f"(d[24]), "+f"(d[25]), "+f"(d[26]), "+f"(d[27]), "+f"(d[28]), "+f"(d[29]), "+f"(d[30]), "+f"(d[31]), "+f"(d[32]), "+f"(d[33]), "+f"(d[34]), "+f"(d[35]), "+f"(d[36]), "+f"(d[37]), "+f"(d[38]), "+f"(d[39]), "+f"(d[40]), "+f"(d[41]), "+f"(d[42]), "+f"(d[43]), "+f"(d[44]), "+f"(d[45]), "+f"(d[46]), "+f"(d[47])
    : "l"(a), "l"(ao), "l"(b), "l"(bo), "r"(sd), "n"(TA), "n"(TB));
}
template <int TA, int TB, int SZ>
__device__ __forceinline__ void wgmma_n128(float (&d)[SZ], uint64_t a, uint64_t ao, uint64_t b, uint64_t bo, int sd) {
  asm volatile("{ .reg .pred p; .reg .b64 da, db; setp.ne.b32 p, %68, 0; add.u64 da, %64, %65; add.u64 db, %66, %67;\n"
    "wgmma.mma_async.sync.aligned.m64n128k16.f32.bf16.bf16 {%0, %1, %2, %3, %4, %5, %6, %7, %8, %9, %10, %11, %12, %13, %14, %15, %16, %17, %18, %19, %20, %21, %22, %23, %24, %25, %26, %27, %28, %29, %30, %31, %32, %33, %34, %35, %36, %37, %38, %39, %40, %41, %42, %43, %44, %45, %46, %47, %48, %49, %50, %51, %52, %53, %54, %55, %56, %57, %58, %59, %60, %61, %62, %63}, da, db, p, 1, 1, %69, %70; }"
    : "+f"(d[0]), "+f"(d[1]), "+f"(d[2]), "+f"(d[3]), "+f"(d[4]), "+f"(d[5]), "+f"(d[6]), "+f"(d[7]), "+f"(d[8]), "+f"(d[9]), "+f"(d[10]), "+f"(d[11]), "+f"(d[12]), "+f"(d[13]), "+f"(d[14]), "+f"(d[15]), "+f"(d[16]), "+f"(d[17]), "+f"(d[18]), "+f"(d[19]), "+f"(d[20]), "+f"(d[21]), "+f"(d[22]), "+f"(d[23]), "+f"(d[24]), "+f"(d[25]), "+f"(d[26]), "+f"(d[27]), "+f"(d[28]), "+f"(d[29]), "+f"(d[30]), "+f"(d[31]), "+f"(d[32]), "+f"(d[33]), "+f"(d[34]), "+f"(d[35]), "+f"(d[36]), "+f"(d[37]), "+f"(d[38]), "+f"(d[39]), "+f"(d[40]), "+f"(d[41]), "+f"(d[42]), "+f"(d[43]), "+f"(d[44]), "+f"(d[45]), "+f"(d[46]), "+f"(d[47]), "+f"(d[48]), "+f"(d[49]), "+f"(d[50]), "+f"(d[51]), "+f"(d[52]), "+f"(d[53]), "+f"(d[54]), "+f"(d[55]), "+f"(d[56]), "+f"(d[57]), "+f"(d[58]), "+f"(d[59]), "+f"(d[60]), "+f"(d[61]), "+f"(d[62]), "+f"(d[63])
    : "l"(a), "l"(ao), "l"(b), "l"(bo), "r"(sd), "n"(TA), "n"(TB));
}
template <int TB = 0>
__device__ __forceinline__ void wgmma_rs_n32(float (&d)[64], const uint32_t* a, uint64_t b, uint64_t bo, int sd) {
  asm volatile("{ .reg .pred p; .reg .b64 db; setp.ne.b32 p, %22, 0; add.u64 db, %20, %21;\n"
    "wgmma.mma_async.sync.aligned.m64n32k16.f32.bf16.bf16 {%0, %1, %2, %3, %4, %5, %6, %7, %8, %9, %10, %11, %12, %13, %14, %15}, {%16, %17, %18, %19}, db, p, 1, 1, %23; }"
    : "+f"(d[48]), "+f"(d[49]), "+f"(d[50]), "+f"(d[51]), "+f"(d[52]), "+f"(d[53]), "+f"(d[54]), "+f"(d[55]), "+f"(d[56]), "+f"(d[57]), "+f"(d[58]), "+f"(d[59]), "+f"(d[60]), "+f"(d[61]), "+f"(d[62]), "+f"(d[63])
    : "r"(a[0]), "r"(a[1]), "r"(a[2]), "r"(a[3]), "l"(b), "l"(bo), "r"(sd), "n"(TB));
}
template <int TB = 0>
__device__ __forceinline__ void wgmma_rs_n64(float (&d)[64], const uint32_t* a, uint64_t b, uint64_t bo, int sd) {
  asm volatile("{ .reg .pred p; .reg .b64 db; setp.ne.b32 p, %38, 0; add.u64 db, %36, %37;\n"
    "wgmma.mma_async.sync.aligned.m64n64k16.f32.bf16.bf16 {%0, %1, %2, %3, %4, %5, %6, %7, %8, %9, %10, %11, %12, %13, %14, %15, %16, %17, %18, %19, %20, %21, %22, %23, %24, %25, %26, %27, %28, %29, %30, %31}, {%32, %33, %34, %35}, db, p, 1, 1, %39; }"
    : "+f"(d[32]), "+f"(d[33]), "+f"(d[34]), "+f"(d[35]), "+f"(d[36]), "+f"(d[37]), "+f"(d[38]), "+f"(d[39]), "+f"(d[40]), "+f"(d[41]), "+f"(d[42]), "+f"(d[43]), "+f"(d[44]), "+f"(d[45]), "+f"(d[46]), "+f"(d[47]), "+f"(d[48]), "+f"(d[49]), "+f"(d[50]), "+f"(d[51]), "+f"(d[52]), "+f"(d[53]), "+f"(d[54]), "+f"(d[55]), "+f"(d[56]), "+f"(d[57]), "+f"(d[58]), "+f"(d[59]), "+f"(d[60]), "+f"(d[61]), "+f"(d[62]), "+f"(d[63])
    : "r"(a[0]), "r"(a[1]), "r"(a[2]), "r"(a[3]), "l"(b), "l"(bo), "r"(sd), "n"(TB));
}
template <int TB = 0>
__device__ __forceinline__ void wgmma_rs_n96(float (&d)[64], const uint32_t* a, uint64_t b, uint64_t bo, int sd) {
  asm volatile("{ .reg .pred p; .reg .b64 db; setp.ne.b32 p, %54, 0; add.u64 db, %52, %53;\n"
    "wgmma.mma_async.sync.aligned.m64n96k16.f32.bf16.bf16 {%0, %1, %2, %3, %4, %5, %6, %7, %8, %9, %10, %11, %12, %13, %14, %15, %16, %17, %18, %19, %20, %21, %22, %23, %24, %25, %26, %27, %28, %29, %30, %31, %32, %33, %34, %35, %36, %37, %38, %39, %40, %41, %42, %43, %44, %45, %46, %47}, {%48, %49, %50, %51}, db, p, 1, 1, %55; }"
    : "+f"(d[16]), "+f"(d[17]), "+f"(d[18]), "+f"(d[19]), "+f"(d[20]), "+f"(d[21]), "+f"(d[22]), "+f"(d[23]), "+f"(d[24]), "+f"(d[25]), "+f"(d[26]), "+f"(d[27]), "+f"(d[28]), "+f"(d[29]), "+f"(d[30]), "+f"(d[31]), "+f"(d[32]), "+f"(d[33]), "+f"(d[34]), "+f"(d[35]), "+f"(d[36]), "+f"(d[37]), "+f"(d[38]), "+f"(d[39]), "+f"(d[40]), "+f"(d[41]), "+f"(d[42]), "+f"(d[43]), "+f"(d[44]), "+f"(d[45]), "+f"(d[46]), "+f"(d[47]), "+f"(d[48]), "+f"(d[49]), "+f"(d[50]), "+f"(d[51]), "+f"(d[52]), "+f"(d[53]), "+f"(d[54]), "+f"(d[55]), "+f"(d[56]), "+f"(d[57]), "+f"(d[58]), "+f"(d[59]), "+f"(d[60]), "+f"(d[61]), "+f"(d[62]), "+f"(d[63])
    : "r"(a[0]), "r"(a[1]), "r"(a[2]), "r"(a[3]), "l"(b), "l"(bo), "r"(sd), "n"(TB));
}
template <int TB = 0>
__device__ __forceinline__ void wgmma_rs_n128(float (&d)[64], const uint32_t* a, uint64_t b, uint64_t bo, int sd) {
  asm volatile("{ .reg .pred p; .reg .b64 db; setp.ne.b32 p, %70, 0; add.u64 db, %68, %69;\n"
    "wgmma.mma_async.sync.aligned.m64n128k16.f32.bf16.bf16 {%0, %1, %2, %3, %4, %5, %6, %7, %8, %9, %10, %11, %12, %13, %14, %15, %16, %17, %18, %19, %20, %21, %22, %23, %24, %25, %26, %27, %28, %29, %30, %31, %32, %33, %34, %35, %36, %37, %38, %39, %40, %41, %42, %43, %44, %45, %46, %47, %48, %49, %50, %51, %52, %53, %54, %55, %56, %57, %58, %59, %60, %61, %62, %63}, {%64, %65, %66, %67}, db, p, 1, 1, %71; }"
    : "+f"(d[0]), "+f"(d[1]), "+f"(d[2]), "+f"(d[3]), "+f"(d[4]), "+f"(d[5]), "+f"(d[6]), "+f"(d[7]), "+f"(d[8]), "+f"(d[9]), "+f"(d[10]), "+f"(d[11]), "+f"(d[12]), "+f"(d[13]), "+f"(d[14]), "+f"(d[15]), "+f"(d[16]), "+f"(d[17]), "+f"(d[18]), "+f"(d[19]), "+f"(d[20]), "+f"(d[21]), "+f"(d[22]), "+f"(d[23]), "+f"(d[24]), "+f"(d[25]), "+f"(d[26]), "+f"(d[27]), "+f"(d[28]), "+f"(d[29]), "+f"(d[30]), "+f"(d[31]), "+f"(d[32]), "+f"(d[33]), "+f"(d[34]), "+f"(d[35]), "+f"(d[36]), "+f"(d[37]), "+f"(d[38]), "+f"(d[39]), "+f"(d[40]), "+f"(d[41]), "+f"(d[42]), "+f"(d[43]), "+f"(d[44]), "+f"(d[45]), "+f"(d[46]), "+f"(d[47]), "+f"(d[48]), "+f"(d[49]), "+f"(d[50]), "+f"(d[51]), "+f"(d[52]), "+f"(d[53]), "+f"(d[54]), "+f"(d[55]), "+f"(d[56]), "+f"(d[57]), "+f"(d[58]), "+f"(d[59]), "+f"(d[60]), "+f"(d[61]), "+f"(d[62]), "+f"(d[63])
    : "r"(a[0]), "r"(a[1]), "r"(a[2]), "r"(a[3]), "l"(b), "l"(bo), "r"(sd), "n"(TB));
}

__device__ __forceinline__ void st_either(int loc, uint32_t a, uint32_t x, uint32_t y, uint32_t z, uint32_t w, uint32_t bar) {
  if (loc == 1) asm volatile("st.shared.v4.b32 [%0], {%1,%2,%3,%4};" :: "r"(a), "r"(x), "r"(y), "r"(z), "r"(w) : "memory");
  if (loc == 0) st_async4(a, x, y, z, w, bar);
}
__device__ __forceinline__ void prep_task(int loc, uint32_t src, uint32_t dst, uint32_t bar, uint32_t w0, uint32_t w1, uint32_t w2, uint32_t w3) {
  uint32_t k[12], u[9];
#pragma unroll
  for (int j = 0; j < 12; j++) k[j] = lds32(j < 4 ? src + (4 + j) * 528 - 16 : src + (j - 4) * 528);
#pragma unroll
  for (int j = 0; j < 9; j++) u[j] = lds32(j < 1 ? src + 4224 + 7 * 528 - 16 : src + 4224 + (j - 1) * 528);
#pragma unroll
  for (int j = 0; j < 9; j++) {
    uint32_t s = bmul(k[j], w3);
    s = bfma(k[j + 1], w2, s); s = bfma(k[j + 2], w1, s); s = bfma(k[j + 3], w0, s);
    u[j] = bmul(s, u[j]);
  }
#pragma unroll
  for (int c = 0; c < 2; c++) {
    const uint32_t sel = c ? 0x7632 : 0x5410;
    st_either(loc, dst + c * U_PITCH, __byte_perm(u[2], u[1], sel), __byte_perm(u[4], u[3], sel), __byte_perm(u[6], u[5], sel), __byte_perm(u[8], u[7], sel), bar);
    st_either(loc, dst + c * U_PITCH + U_ODD, __byte_perm(u[1], u[0], sel), __byte_perm(u[3], u[2], sel), __byte_perm(u[5], u[4], sel), __byte_perm(u[7], u[6], sel), bar);
  }
}

template <int S, int C0, int NK>
__device__ __forceinline__ void frag_load(uint32_t (&P)[4 * NK], uint32_t ua, uint32_t z) {
  P[2] = lds32(ua + 1024 * S + 32 * C0 - 16);
#pragma unroll
  for (int kk = 0; kk < NK; kk++) { P[4 * kk] = lds32(ua + 1024 * S + 32 * (C0 + kk)); P[4 * kk + 1] = lds32(ua + 1024 * S + 32 * (C0 + kk) + 16); }
#pragma unroll
  for (int kk = 0; kk < NK; kk++) { P[4 * kk + 3] = P[4 * kk] ^ z; if (kk) P[4 * kk + 2] = P[4 * kk - 3] ^ z; }
#pragma unroll
  for (int i = 0; i < 4 * NK; i++) asm volatile("" : "+r"(P[i]) :: "memory");
}
template <int S, int C0, int NK, int CH>
__device__ __forceinline__ void conv_issue(float (&acc)[64], const uint32_t (&P)[4 * NK], uint64_t& db, uint64_t z64) {
  if (S > 0 && C0 == 0) reg_rename<16 * S, 64>(acc);
  if (C0 == 0 && CH == 0) db = fresh(db, z64);
  wg_fence();
#pragma unroll
  for (int kk = 0; kk < NK; kk++) {
    const uint64_t o = 16 - 2 * (C0 + kk) + CH * (T_PITCH / 8);
    if (S == 0) wgmma_rs_n128<0>(acc, &P[4 * kk], db, o, C0 + kk != 0);
    if (S == 1) wgmma_rs_n96<0>(acc, &P[4 * kk], db, o, 1);
    if (S == 2) wgmma_rs_n64<0>(acc, &P[4 * kk], db, o, 1);
    if (S == 3) wgmma_rs_n32<0>(acc, &P[4 * kk], db, o, 1);
  }
  wg_commit();
}
template <int S>
__device__ __forceinline__ void conv_dump(float (&acc)[64], uint32_t xw, int wl) {
  reg_fence<16 * S, 16 * S + 16>(acc);
#pragma unroll
  for (int r = 0; r < 3; r++) {
    const int i = 16 * S + 4 * (r + 1);
    if (S < 3 || wl + r + 1 < 4) sts64(xw + (4 * S + r + 1) * 768 + r * 256, pack2(acc[i], acc[i + 1]), pack2(acc[i + 2], acc[i + 3]));
  }
}
template <int S>
__device__ __forceinline__ void conv_reduce(float (&y)[4], const float (&acc)[64], uint32_t xw, int wl) {
#pragma unroll
  for (int i = 0; i < 4; i++) y[i] = acc[16 * S + i];
  uint2 v[3];
#pragma unroll
  for (int r = 0; r < 3; r++) {
    v[r] = make_uint2(0u, 0u);
    if (S > 0 || r < wl) v[r] = lds64(xw + 4 * S * 768 + r * 256);
  }
#pragma unroll
  for (int r = 0; r < 3; r++) { y[0] += blo(v[r].x); y[1] += bhi(v[r].x); y[2] += blo(v[r].y); y[3] += bhi(v[r].y); }
}
struct FinCtx { uint32_t um, xt, st, DA, DB; uint32_t *hA, *hB; };
template <int S>
__device__ __forceinline__ void conv_z(uint32_t (&zz)[4], const FinCtx& c, const float (&aA)[64], const float (&aB)[64], uint32_t xA, uint32_t xB, int wl) {
  uint32_t u[4];
  float ya[4], yb[4];
  ldsm4t(c.um + S * 1024, u[0], u[1], u[2], u[3]);
  conv_reduce<S>(ya, aA, xA, wl); conv_reduce<S>(yb, aB, xB, wl);
  zz[0] = bfma(u[0], c.DA, pack2(ya[0], ya[1])); zz[1] = bfma(u[1], c.DA, pack2(ya[2], ya[3]));
  zz[2] = bfma(u[2], c.DB, pack2(yb[0], yb[1])); zz[3] = bfma(u[3], c.DB, pack2(yb[2], yb[3]));
}
template <int S>
__device__ __forceinline__ void conv_fin(const FinCtx& c, const uint32_t (&zz)[4]) {
  constexpr uint32_t XO = (S < 2 ? OFF_XTE : OFF_XTL) + (S & 1) * 4096, SO = (S < 2 ? OFF_STE : OFF_STL) + (S & 1) * 2048;
#pragma unroll
  for (int h = 0; h < 2; h++) {
    uint2 sv = lds64(c.st + SO + h * 256);
    uint32_t xa = lds32(c.xt + XO + h * 512), xb = lds32((c.xt ^ 64) + XO + h * 512);
    c.hA[(8 * S + h) * (D_ * 32)] = bfma(bfma(xa, sv.x, sv.y), zz[h], xa);
    c.hB[(8 * S + h) * (D_ * 32)] = bfma(bfma(xb, sv.x, sv.y), zz[2 + h], xb);
  }
}

struct RowC { float nm, k1, k2, hs; };
__device__ __forceinline__ float geglu(float g, float u, float cg, float cu, const RowC& r) {
  float gc = fmaf(r.nm, cg, g), uc = fmaf(r.nm, cu, u);
  float in = gc * fmaf(gc * gc, r.k2, r.k1);
  float t; asm("tanh.approx.f32 %0, %1;" : "=f"(t) : "f"(in));
  float pr = gc * uc;
  return fmaf(pr, t, pr);
}
template <int GI, int UI, int N>
__device__ __forceinline__ void epi_group(const float (&acc)[N], const float4& c, const RowC& r0, const RowC& r1, uint32_t* dst, uint32_t* keep) {
  uint32_t lo = pack2(geglu(acc[GI], acc[UI], c.x, c.z, r0), geglu(acc[GI + 1], acc[UI + 1], c.y, c.w, r0));
  uint32_t hi = pack2(geglu(acc[GI + 2], acc[UI + 2], c.x, c.z, r1), geglu(acc[GI + 3], acc[UI + 3], c.y, c.w, r1));
  dst[0] = lo; dst[32] = hi;
  keep[0] = lo; keep[1] = hi;
}

__device__ __forceinline__ void mma_ones(float (&d)[4], uint32_t a0, uint32_t a1, uint32_t a2, uint32_t a3) {
  asm volatile("mma.sync.aligned.m16n8k16.row.col.f32.bf16.bf16.f32 {%0,%1,%2,%3}, {%4,%5,%6,%7}, {%8,%8}, {%0,%1,%2,%3};"
    : "+f"(d[0]), "+f"(d[1]), "+f"(d[2]), "+f"(d[3]) : "r"(a0), "r"(a1), "r"(a2), "r"(a3), "r"(0x3f803f80));
}

struct Params {
  const uint16_t *shift_k, *ssm_D, *wd;
  uint16_t* out;
  Scratch* scr;
  uint8_t map[NCTA];
  uint64_t z64;
};

__global__ void __launch_bounds__(NTHR, 1)
fused_kernel(const __grid_constant__ Params p, const __grid_constant__ CUtensorMap tmXR, const __grid_constant__ CUtensorMap tmT, const __grid_constant__ CUtensorMap tmK, const __grid_constant__ CUtensorMap tmV,
             const __grid_constant__ CUtensorMap tmG, const __grid_constant__ CUtensorMap tmU,
             const __grid_constant__ CUtensorMap tmG32, const __grid_constant__ CUtensorMap tmU32,
             const __grid_constant__ CUtensorMap tmD, const __grid_constant__ CUtensorMap tmX, const __grid_constant__ CUtensorMap tmD16) {
  extern __shared__ __align__(1024) uint8_t smem[];
  const uint32_t sb = s2u(smem);
  const int xb = blockIdx.x;
  auto x_load = [&]() {
    const uint32_t b = sb + OFF_BAR + B_XR * 8;
    mbar_expect(b, 16384);
    asm volatile("cp.async.bulk.tensor.4d.shared::cluster.global.mbarrier::complete_tx::bytes [%0], [%1, {%3, %4, %5, %3}], [%2];"
                 :: "r"(sb + OFF_XR), "l"(&tmXR), "r"(b), "r"(0), "r"((xb & 7) * 2), "r"(xb & ~7) : "memory");
  };

  const int rank = blockIdx.x & 1;
  auto BAR = [&](int i) { return sb + OFF_BAR + i * 8; };
  auto kv_load = [&](int pc, int pr) {
    uint32_t b = BAR(B_KV + pc), d = sb + OFF_KV + pc * KV_PIECE;
    int run0 = pc * 64 + rank * 32 - 1;
    mbar_expect(b, KV_PIECE);
    tma3d(d, &tmK, pr * 8, run0, 0, b);
    tma3d(d + 4224, &tmV, pr * 8, run0, 0, b);
  };
  if (threadIdx.x < 32) {
    if (elect()) {
      mbar_init(BAR(B_XR), 1); mbar_init(BAR(B_SK), 1); mbar_init(BAR(B_KV), 1); mbar_init(BAR(B_TAP), 1); mbar_init(BAR(B_TAP + 1), 1);
      x_load();
      const int cl = blockIdx.x >> 1, q7 = ((cl - 36) * 37) >> 8;
      const int pr = cl < 4 ? cl : cl < 36 ? 4 + ((cl - 4) & 7) * 4 + ((cl - 4) >> 3) : 4 * cl - 108 - 27 * q7;
      mbar_expect(BAR(B_SK), 80);
      bulk_ld(sb + OFF_SK, p.shift_k + pr * 32, 64, BAR(B_SK));
      bulk_ld(sb + OFF_SK + 64, p.ssm_D + pr * 8, 16, BAR(B_SK));
      kv_load(0, pr);
#pragma unroll
      for (int i = 0; i < 2; i++) {
        mbar_expect(BAR(B_TAP + i), 2 * T_PITCH);
        tma3d(sb + OFF_TAP + i * 2 * T_PITCH, &tmT, 0, -1, pr * 8 + rank * 4 + 2 * i, BAR(B_TAP + i));
      }
    }
    __syncwarp();
  }
  const int bid = p.map[blockIdx.x], pair = bid >> 1;
  const int tile = bid >> 3, js = bid & 7;
  const int tid = (threadIdx.x + 384) & 511, lane = tid & 31;
  const int warp = __shfl_sync(0xffffffffu, tid >> 5, 0);
  const int g = lane >> 2, q = lane & 3;
  if (warp >= 8) {
    if (warp != 12 && elect()) {
      const int cnt = warp < 10 ? 8 : (warp < 12 ? 4 : 1), cnt0 = warp == 13 ? 5 : cnt;
#pragma unroll
      for (int i = 0; i < 10; i++) mbar_init(BAR((warp - 8) * 10 + i), i < 4 ? cnt0 : (warp == 9 || (i >= 6 && warp == 11) ? 1 : cnt));
      asm volatile("fence.mbarrier_init.release.cluster;" ::: "memory");
      if (warp == 14) {
#pragma unroll
        for (int i = 0; i < 3; i++) { mbar_init(BAR(B_KV + 1 + i), 1); mbar_init(BAR(B_CS + i), 1); }
      }
      if (warp == 13) {
#pragma unroll
        for (int i = 0; i < 8; i++) mbar_expect(BAR(B_U + i), i < 4 ? 4096 : i < 6 ? 8192 : 512);
      }
    }
    __syncwarp();
  } else {
    if (tid < 64) sts32(sb + OFF_U + (tid >> 4) * U_PITCH + ((tid >> 3) & 1) * U_ODD + (tid & 7) * 4, 0u);
  }
  __syncthreads();
  asm volatile("barrier.cluster.arrive.relaxed.aligned;" ::: "memory");

  auto pub_cs = [&]() {
    mbar_wait_bounded(BAR(B_CSD), 0);
    if (bid < 86) {
      const int which = bid >= 43, f = (bid - which * 43) * 32 + lane;
      const uint32_t a = sb + OFF_CS + lane * 4;
      const float sum = __uint_as_float(lds32(a)) + __uint_as_float(lds32(a + 128)) + __uint_as_float(lds32(a + 256)) + __uint_as_float(lds32(a + 384));
      const uint32_t lo = __shfl_up_sync(0xffffffffu, pack2(sum, 0.f), 1), sb_ = __float_as_uint(sum);
      const uint32_t hi = (sb_ & 0x7fffffffu) < 0x10000u ? sb_ : sb_ - lo + 0x8000u;
      if (lane & 1) p.scr->cs[(f >> 4) * 16 + ((f >> 1) & 3) * 4 + ((f >> 3) & 1) * 2 + which] = (hi & 0xffff0000u) | lo;
      __syncwarp();
    }
    if (elect()) signal_gpu(&p.scr->cnt[CNT_C * 32]);
    __syncwarp();
  };
  if (warp < 8) {
    asm volatile("setmaxnreg.inc.sync.aligned.u32 %0;" :: "n"(REG_C));
    asm volatile("barrier.cluster.wait.aligned;" ::: "memory");
    uint2 small = make_uint2(0u, 0u);
#pragma unroll 1
    for (int pass = 0; pass < 2; pass++) {
      if (pass) mbar_wait(BAR(B_XR), 0);
      const int mi = lane >> 3, rho = lane & 7;
      const int t = (rho & 1) + 4 * (rho >> 1) + 2 * (mi & 1);
      const int xrow = 2 * (t & 7) + ((t >> 3) ^ 1);
      const uint32_t xa = sb + OFF_XR + warp * 2048 + xrow * 128 + (((mi >> 1) ^ (xrow & 7)) * 16);
      const uint32_t xo = sb + OFF_XST + warp * 2048 + (g ^ (xb & 3)) * 32 + q * 8;
#pragma unroll
      for (int i = 0; i < 4; i++) {
        uint32_t m0, m1, m2, m3;
        ldsm4t(xa ^ (i * 32), m0, m1, m2, m3);
        sts64(xo + i * 512, m0, m1);
        sts64(xo + i * 512 + 256, m2, m3);
      }
      const int r = tid >> 4;
      const uint32_t ra = sb + OFF_XR + (2 * (r & 7) + ((r >> 3) ^ 1)) * 128 + (mi & 1) * 2048 + rho * 16;
      float f[32];
#pragma unroll
      for (int i = 0; i < 4; i++) {
        uint4 v = lds128(ra + i * 4096);
        f[8 * i] = blo(v.x); f[8 * i + 1] = bhi(v.x); f[8 * i + 2] = blo(v.y); f[8 * i + 3] = bhi(v.y);
        f[8 * i + 4] = blo(v.z); f[8 * i + 5] = bhi(v.z); f[8 * i + 6] = blo(v.w); f[8 * i + 7] = bhi(v.w);
      }
      const float c0 = blo(lds32(sb + OFF_XR + (2 * (r & 7) + ((r >> 3) ^ 1)) * 128));
      float sa = 0.f, sc = 0.f, qa = 0.f, qc = 0.f;
#pragma unroll
      for (int i = 0; i < 16; i++) { float d0 = f[2 * i] - c0, d1 = f[2 * i + 1] - c0; sa += d0; sc += d1; qa = fmaf(d0, d0, qa); qc = fmaf(d1, d1, qc); }
      sa += sc; qa += qc;
#pragma unroll
      for (int o = 1; o < 16; o <<= 1) { sa += __shfl_xor_sync(0xffffffffu, sa, o); qa += __shfl_xor_sync(0xffffffffu, qa, o); }
      const float md = sa * (1.f / D_), mean = md + c0;
      const float rs = blo(pack2(rsqrtf(fmaxf(fmaf(-md, md, qa * (1.f / D_)), 0.f) + 1e-5f), 0.f));
      const uint32_t me = pack2(rs, -mean * rs), ot = __shfl_xor_sync(0xffffffffu, me, 16);
      if (lane == 0) sts64(sb + OFF_CS + warp * 8, __byte_perm(me, ot, 0x5410), __byte_perm(me, ot, 0x7632));
      __syncwarp();
      if (lane == 0 && pass) mbar_arrive(BAR(B_SIGX));
      if (pass) { float w0;
        asm volatile("{ .reg .f32 a, b, c; mma.sync.aligned.m16n8k8.row.col.f32.bf16.bf16.f32 {%0,a,b,c}, {%1,%1}, {%1}, {%2,%2,%2,%2}; }"
                     : "=f"(w0) : "r"(blockIdx.x >> 16), "f"(0.f));
        small.x ^= __float_as_uint(w0); }
    }
    const int hw = warp >> 2, wl = warp & 3;
    {
      const int chA = bid * 4 + hw, chB = chA + 2;
      const int ig = g ^ 1;
      const uint32_t uA = sb + OFF_U + hw * U_PITCH + ((ig & 1) ? 0 : U_ODD) + 32 + ((ig - 2 * q) >> 1) * 4 + wl * 256;
      const uint32_t uB = uA + 2 * U_PITCH;
      uint64_t dT = mkdesc(sb + OFF_TAP + hw * T_PITCH, 16, 256, 3);
      const uint32_t z = blockIdx.x >> 16;
      const uint32_t xA = sb + OFF_XCH + (hw * 32 + wl) * 768 + lane * 8, xB = xA + 16 * 768;
      FinCtx fc;
      fc.um = sb + OFF_U + (hw + 2 * (lane >> 4)) * U_PITCH + 32 + wl * 256 + (lane & 7) * 32 + ((lane >> 3) & 1) * 16;
      fc.xt = sb + wl * 1024 + (lane >> 3) * 128 + (hw ^ (lane >> 3)) * 32 + (lane & 7) * 4;
      fc.st = sb + wl * 512 + lane * 8;
      mbar_wait(BAR(B_SK), 0);
      { const uint2 d4 = lds64(sb + OFF_SK + 64 + rank * 8); small.x ^= d4.x; small.y = d4.y; }
      fc.DA = __byte_perm(small.x, 0, hw ? 0x3232 : 0x1010); fc.DB = __byte_perm(small.y, 0, hw ? 0x3232 : 0x1010);
      fc.hA = (uint32_t*)p.scr->hT + (size_t)wl * 2 * (D_ * 32) + chA * 32 + ((g ^ (chA & 7)) * 4) + q;
      fc.hB = (uint32_t*)p.scr->hT + (size_t)wl * 2 * (D_ * 32) + chB * 32 + ((g ^ (chB & 7)) * 4) + q;
      auto tap_fix = [&](int i) {
        const uint32_t a = sb + OFF_TAP + (hw + 2 * i) * T_PITCH + 256 + ((tid & 127) >> 3) * 256 + 128 + (tid & 7) * 16;
        mbar_wait(BAR(B_TAP + i), 0);
        const uint4 v = lds128(a);
        __syncwarp();
        asm volatile("st.shared.v4.b32 [%0], {%1,%2,%3,%4};" :: "r"(a ^ 16), "r"(v.x), "r"(v.y), "r"(v.z), "r"(v.w) : "memory");
        fence_async_s();
        bar_sync(1 + hw, 128);
      };
      tap_fix(0);
      float aA[64], aB[64];
      uint32_t z0[4], z1[4];
      {
        uint32_t P[16], Q[16];
        mbar_wait_cluster(BAR(B_U + 0), 0);
        frag_load<0, 0, 4>(P, uA, z); conv_issue<0, 0, 4, 0>(aA, P, dT, p.z64);
        frag_load<0, 4, 4>(Q, uA, z); conv_issue<0, 4, 4, 0>(aA, Q, dT, p.z64);
        tap_fix(1);
        wg_wait<1>(); frag_load<0, 0, 4>(P, uB, z); conv_issue<0, 0, 4, 1>(aB, P, dT, p.z64);
        wg_wait<1>(); frag_load<0, 4, 4>(Q, uB, z); conv_issue<0, 4, 4, 1>(aB, Q, dT, p.z64);
        conv_dump<0>(aA, xA, wl);
        mbar_wait_cluster(BAR(B_U + 1), 0);
        wg_wait<1>(); frag_load<1, 0, 4>(P, uA, z); conv_issue<1, 0, 4, 0>(aA, P, dT, p.z64);
        wg_wait<1>(); frag_load<1, 4, 4>(Q, uA, z); conv_issue<1, 4, 4, 0>(aA, Q, dT, p.z64);
        conv_dump<0>(aB, xB, wl);
        wg_wait<1>(); frag_load<1, 0, 4>(P, uB, z); conv_issue<1, 0, 4, 1>(aB, P, dT, p.z64);
        bar_sync(1 + hw, 128);
        conv_z<0>(z0, fc, aA, aB, xA, xB, wl);
        wg_wait<1>(); frag_load<1, 4, 4>(Q, uB, z); conv_issue<1, 4, 4, 1>(aB, Q, dT, p.z64);
        conv_dump<1>(aA, xA, wl);
      }
      {
        uint32_t P[32], Q[32], R[32];
        mbar_wait_cluster(BAR(B_U + 2), 0);
        wg_wait<1>(); frag_load<2, 0, 8>(P, uA, z); conv_issue<2, 0, 8, 0>(aA, P, dT, p.z64);
        frag_load<2, 0, 8>(Q, uB, z); wg_wait<1>(); conv_issue<2, 0, 8, 1>(aB, Q, dT, p.z64);
        conv_dump<1>(aB, xB, wl);
        bar_sync(1 + hw, 128);
        conv_z<1>(z1, fc, aA, aB, xA, xB, wl);
        mbar_wait(BAR(B_XT), 0);
        conv_fin<0>(fc, z0);
        conv_fin<1>(fc, z1);
        __syncwarp();
        if (lane == 0) mbar_arrive(BAR(B_SIGE + 0));
        mbar_wait_cluster(BAR(B_U + 3), 0);
        frag_load<3, 0, 8>(R, uA, z); wg_wait<1>(); conv_issue<3, 0, 8, 0>(aA, R, dT, p.z64);
        frag_load<3, 0, 8>(P, uB, z); wg_wait<1>(); conv_issue<3, 0, 8, 1>(aB, P, dT, p.z64);
        conv_dump<2>(aA, xA, wl); conv_dump<2>(aB, xB, wl);
        wg_wait<0>();
        conv_dump<3>(aA, xA, wl); conv_dump<3>(aB, xB, wl);
        bar_sync(1 + hw, 128);
        mbar_wait(BAR(B_XT + 1), 0);
        conv_z<2>(z0, fc, aA, aB, xA, xB, wl);
        conv_fin<2>(fc, z0);
        conv_z<3>(z1, fc, aA, aB, xA, xB, wl);
        conv_fin<3>(fc, z1);
        __syncwarp();
        if (lane == 0) mbar_arrive(BAR(B_SIGE + 1));
      }
    }
    const int blk = tile + 16 * hw;
    const uint32_t aw = sb + OFF_A + hw * 65536;
    const uint32_t fullA = BAR(B_FULLA + hw * 8), emptyA = BAR(B_EMPTYA + hw * 6);
    const uint32_t lmo = aw + (((lane >> 4) * 8 + (lane & 7)) * 128) + (((2 * wl + ((lane >> 3) & 1)) ^ (lane & 7)) * 16);
    uint64_t da = fresh(mkdesc(aw - 16, 0, 1024, 1), p.z64), db = fresh(mkdesc(sb + OFF_RING - 16, 8192, 1024, 1), p.z64);
    float acc1[64], acc2[64];
    RowC r0, r1;
    const uint32_t csa = sb + OFF_CS + q * 16;
    float4 cc[22];
    auto ldcs = [&](int i0, int i1) {
#pragma unroll
      for (int i = i0; i < i1; i += 2) {
        const uint4 v = lds128(csa + i * 32);
        cc[i] = make_float4(blo(v.x), __uint_as_float(v.x), blo(v.y), __uint_as_float(v.y));
        cc[i + 1] = make_float4(blo(v.z), __uint_as_float(v.z), blo(v.w), __uint_as_float(v.w));
      }
    };
    uint32_t res[16], own1[16], own2[16], own3[12];
    auto ldres = [&]() {
#pragma unroll
      for (int kk = 0; kk < 4; kk++) ldsm4t(lmo + js * 8192 + kk * 2048, res[4 * kk], res[4 * kk + 1], res[4 * kk + 2], res[4 * kk + 3]);
    };
#pragma unroll
    for (int s = 0; s < 8; s++) {
      mbar_wait(fullA + s * 8, 0);
      mbar_wait(BAR(B_FULLR + s % 6), s >= 6);
      wg_fence();
#pragma unroll
      for (int kk = 0; kk < 4; kk++) wgmma_n128<1, 1>(acc1, da, 1 + s * 512 + kk * 128, db, 1 + (s % 6) * 1024 + kk * 128, (s | kk) != 0);
      wg_commit();
      if (s == 3) db = fresh(db, p.z64);
      if (s > 0) { wg_wait<1>(); if (lane == 0) mbar_arrive(BAR(B_EMPTYR + (s - 1) % 6)); }
    }
    uint32_t* hdst = (uint32_t*)p.scr->H + (size_t)blk * (86 * 512) + wl * 64 + lane;
    da = fresh(da, p.z64); db = fresh(db, p.z64);
#pragma unroll
    for (int s = 0; s < 8; s++) {
      const int r = 8 + s, slot = r % 6;
      mbar_wait(BAR(B_FULLR + slot), (r / 6) & 1);
      wg_fence();
#pragma unroll
      for (int kk = 0; kk < 4; kk++) wgmma_n128<1, 1>(acc2, da, 1 + s * 512 + kk * 128, db, 1 + slot * 1024 + kk * 128, (s | kk) != 0);
      if (s == 3) db = fresh(db, p.z64);
      wg_commit();
      uint32_t* d = hdst + js * 8 * 256;
      if (s == 0) {
        mbar_wait_cluster(BAR(B_STX + hw), 0);
        auto mk = [](uint2 v) {
          const float rs = __uint_as_float(v.y), r2 = rs * rs;
          RowC r; r.nm = __uint_as_float(v.x); r.k1 = 0.7978845608028654f * rs; r.k2 = 0.044715f * r2 * r.k1; r.hs = 0.5f * r2;
          return r;
        };
        r0 = mk(lds64(sb + OFF_STX + warp * 128 + g * 8)); r1 = mk(lds64(sb + OFF_STX + warp * 128 + 64 + g * 8));
        mbar_wait(BAR(B_CS), 0);
      }
      if (s == 1) reg_fence<0, 64>(acc1);
      static_for<0, 8>([&](auto ic) {
        constexpr int i = decltype(ic)::v;
        if (s == ((0x55443321 >> (4 * i)) & 15)) epi_group<4 * i, 32 + 4 * i>(acc1, cc[i], r0, r1, d + i * 256, &own1[2 * i]);
      });
      if (s == 5) { __syncwarp(); if (lane == 0) mbar_arrive(BAR(B_SIGH + 0)); }
      if (s == 0) ldcs(0, 2);
      if (s >= 2 && s < 5) ldcs(2 * s - 2, 2 * s);
      if (s == 6) ldres();
      if (s >= 6) ldcs(8 + 4 * (s - 6), 12 + 4 * (s - 6));
      wg_wait<1>();
      if (lane == 0) mbar_arrive(BAR(B_EMPTYR + (r - 1) % 6));
    }
    da = fresh(da, p.z64); db = fresh(mkdesc(sb + OFF_RING - 16, 4096, 512, 2), p.z64);
    float acc3[48];
#pragma unroll
    for (int s = 0; s < 8; s++) {
      const int r = 16 + s, slot = r % 6;
      mbar_wait(BAR(B_FULLR + slot), (r / 6) & 1);
      wg_fence();
#pragma unroll
      for (int kk = 0; kk < 4; kk++) wgmma_n96<1, 1>(acc3, da, 1 + s * 512 + kk * 128, db, 1 + slot * 1024 + kk * 64, (s | kk) != 0);
      if (s == 3) db = fresh(db, p.z64);
      wg_commit();
      uint32_t* d = hdst + (64 + js * 8) * 256;
      if (s == 0) {
        wg_wait<1>();
        if (lane == 0) mbar_arrive(BAR(B_EMPTYR + (r - 1) % 6));
        reg_fence<0, 64>(acc2);
      }
      static_for<0, 8>([&](auto ic) {
        constexpr int i = decltype(ic)::v;
        if (s == (i ? i : 1)) epi_group<4 * i, 32 + 4 * i>(acc2, cc[8 + i], r0, r1, d + i * 256, &own2[2 * i]);
      });
      if (s >= 5) ldcs(6 + 2 * s, 8 + 2 * s);
      if (s > 0) {
        wg_wait<1>();
        if (lane == 0) { mbar_arrive(BAR(B_EMPTYR + (r - 1) % 6)); if (s < 7) mbar_arrive(emptyA + (s - 1) * 8); }
      }
    }
    da = fresh(mkdesc(aw - 16, 1024, 128, 0), p.z64); db = fresh(mkdesc(sb + OFF_RING - 16, 8192, 1024, 1), p.z64);
    float acco[64], base[32];
    {
      wg_wait<0>();
      if (lane == 0) {
        mbar_arrive(BAR(B_EMPTYR + 23 % 6));
        asm volatile("mbarrier.arrive.relaxed.cluster.shared::cluster.b64 _, [%0];" :: "r"(mapa(BAR(B_PEER + hw), rank ^ 1)) : "memory");
      }
      reg_fence<0, 48>(acc3);
      uint32_t* d = hdst + (128 + js * 4) * 256;
      uint32_t* dx = hdst + (160 + js * 2) * 256;
      epi_group<0, 16>(acc3, cc[16], r0, r1, d, &own3[0]); epi_group<4, 20>(acc3, cc[17], r0, r1, d + 256, &own3[2]);
      mbar_wait(BAR(B_FULLR), 0);
      wg_fence();
#pragma unroll
      for (int kk = 0; kk < 4; kk++) wgmma_rs_n128<1>(acco, &own1[4 * kk], db, 1 + kk * 128, kk != 0);
      wg_commit();
      epi_group<8, 24>(acc3, cc[18], r0, r1, d + 512, &own3[4]); epi_group<12, 28>(acc3, cc[19], r0, r1, d + 768, &own3[6]);
      own3[8] = own3[9] = own3[10] = own3[11] = 0u;
      if (js < 6) { epi_group<32, 40>(acc3, cc[20], r0, r1, dx, &own3[8]); epi_group<36, 44>(acc3, cc[21], r0, r1, dx + 256, &own3[10]); }
      __syncwarp();
      if (lane == 0) mbar_arrive(BAR(B_SIGH + 1));
#pragma unroll
      for (int s = 1; s < 9; s++) {
        const int slot = s % 6, hsl = s < 4 ? s - 1 : s - 3, hp = s < 5 ? s - 2 : s - 4;
        if (s != 4 && s != 5) mbar_wait(fullA + hsl * 8, 1);
        mbar_wait(BAR(B_FULLR + slot), s >= 6);
        wg_fence();
#pragma unroll
        for (int kk = 0; kk < (s == 5 ? 3 : 4); kk++) {
          if (s == 4) wgmma_rs_n128<1>(acco, &own2[4 * kk], db, 1 + slot * 1024 + kk * 128, 1);
          else if (s == 5) wgmma_rs_n128<1>(acco, &own3[4 * (kk % 3)], db, 1 + slot * 1024 + kk * 128, 1);
          else wgmma_n128<0, 1>(acco, da, 1 + hsl * 512 + kk * 128, db, 1 + slot * 1024 + kk * 128, 1);
        }
        wg_commit();
        if (s == 3) {
          da = fresh(da, p.z64); db = fresh(db, p.z64);
#pragma unroll
          for (int i = 0; i < 16; i++) { base[2 * i] = blo(res[i]); base[2 * i + 1] = bhi(res[i]); }
          reg_fence<0, 32>(base);
        }
        if (s < 8) {
          wg_wait<1>();
          if (lane == 0) { if (s != 1 && s != 5 && s != 6) mbar_arrive(emptyA + hp * 8); if (s < 6) mbar_arrive(BAR(B_EMPTYR + s - 1)); }
        }
      }
    }
    da = fresh(da, p.z64); db = fresh(db, p.z64);
    const uint32_t ob = aw + 6 * 8192 + wl * 2048;
    uint32_t oa;
    { const int orow = 2 * (lane & 7) + (((lane >> 3) & 1) ^ 1); oa = ob + orow * 128 + (((lane >> 4) ^ (orow & 7)) * 16); }
    uint32_t ol = ob + (lane >> 3) * 128 + (((lane & 7) ^ (lane >> 3)) * 16);
    uint16_t* og = p.out + (size_t)((blk >> 1) * 128 + (blk & 1) * 8 + wl * 2 + (lane >> 4) * 16 + ((lane >> 3) & 1)) * D_ + js * 64 + (lane & 7) * 8;
    float accn[32];
    {
      const uint32_t ra = mapa(ob + lane * 16, rank ^ 1), rb = mapa(BAR(B_RECV + hw), rank ^ 1);
      auto send = [&]() {
        reg_fence<0, 64>(acco);
#pragma unroll
        for (int i = 0; i < 4; i++)
          st_async4(ra + i * 512, pack2(acco[32 + 8 * i], acco[33 + 8 * i]), pack2(acco[34 + 8 * i], acco[35 + 8 * i]),
                    pack2(acco[36 + 8 * i], acco[37 + 8 * i]), pack2(acco[38 + 8 * i], acco[39 + 8 * i]), rb);
      };
      mbar_wait_cluster(BAR(B_PEER + hw), 0);
#pragma unroll
      for (int s = 0; s < 4; s++) {
        const int slot = h_slot(6 + s);
        mbar_wait(fullA + slot * 8, h_par(6 + s));
        if ((s & 1) == 0) mbar_wait(BAR(B_FULLR + 3 + s / 2), 1);
        wg_fence();
#pragma unroll
        for (int kk = 0; kk < 4; kk++)
          wgmma_n64<0, 1>(accn, da, 1 + slot * 512 + kk * 128, db, 3073 + s * 512 + kk * 128, (s | kk) != 0);
        wg_commit();
        if (s == 3 && js >= 6) {
          mbar_wait(fullA + h_slot(10) * 8, h_par(10));
          wg_fence();
#pragma unroll
          for (int kk = 0; kk < 2; kk++) wgmma_n64<0, 1>(accn, da, 1 + h_slot(10) * 512 + kk * 128, db, 5121 + 256 + kk * 128, 1);
          wg_commit();
        }
        if (s == 0) { wg_wait<1>(); send(); }
        if (s == 2) {
#pragma unroll
          for (int i = 0; i < 32; i++) base[i] = fmaf(acco[i], (i & 2) ? r1.hs : r0.hs, base[i]);
          reg_fence<0, 32>(base);
        }
      }
    }
    {
      mbar_wait_cluster(BAR(B_RECV + hw), 0);
      if (lane == 0) mbar_arrive(BAR(B_SIG + 5));
#pragma unroll
      for (int i = 0; i < 4; i++) {
        const uint4 o = lds128(ob + lane * 16 + i * 512);
        const uint32_t ov[4] = {o.x, o.y, o.z, o.w};
#pragma unroll
        for (int j = 0; j < 4; j++) {
          const float hs = (j & 1) ? r1.hs : r0.hs;
          base[8 * i + 2 * j] = fmaf(blo(ov[j]), hs, base[8 * i + 2 * j]); base[8 * i + 2 * j + 1] = fmaf(bhi(ov[j]), hs, base[8 * i + 2 * j + 1]);
        }
      }
      reg_fence<0, 32>(base);
      wg_wait<0>();
      reg_fence<0, 32>(accn);
#pragma unroll
      for (int i = 0; i < 32; i++) acco[i] = fmaf(accn[i], (i & 2) ? r1.hs : r0.hs, base[i]);
      __syncwarp();
#pragma unroll
      for (int i = 0; i < 4; i++)
        stsm4(oa ^ (i * 32), pack2(acco[8 * i], acco[8 * i + 1]), pack2(acco[8 * i + 2], acco[8 * i + 3]),
              pack2(acco[8 * i + 4], acco[8 * i + 5]), pack2(acco[8 * i + 6], acco[8 * i + 7]));
      __syncwarp();
#pragma unroll
      for (int i = 0; i < 4; i++) *(uint4*)(og + (size_t)i * 32 * D_) = lds128((ol + i * 512) ^ ((i & 1) * 64));
    }
  } else if (warp < 12) {
    asm volatile("setmaxnreg.dec.sync.aligned.u32 %0;" :: "n"(REG_P));
    const int h = warp - 8;
    uint32_t w0 = 0, w1 = 0, w2 = 0, w3 = 0;
    const uint32_t psrc = sb + OFF_KV + 16 + lane * 4 + h * 128;
    const uint32_t pdst = mapa(sb + OFF_U + (q & 1) * 2 * U_PITCH + 32 + rank * 512 + g * 16 + h * 128, q >> 1), pbar = mapa(BAR(B_U), q >> 1);
    asm volatile("barrier.cluster.wait.aligned;" ::: "memory");
#pragma unroll 1
    for (int pc = -1; pc < 4; pc++) {
      if (pc == 0) {
        mbar_wait(BAR(B_SK), 0);
        const uint4 sk = lds128(sb + OFF_SK + q * 16);
        w0 = __byte_perm(sk.x, sk.z, 0x5410); w1 = __byte_perm(sk.x, sk.z, 0x7632);
        w2 = __byte_perm(sk.y, sk.w, 0x5410); w3 = __byte_perm(sk.y, sk.w, 0x7632);
      }
      if (pc >= 0) mbar_wait(BAR(B_KV + pc), 0);
      prep_task(pc < 0 ? 2 : (q >> 1) == rank, psrc + pc * KV_PIECE, pdst + pc * 1024, pbar + pc * 8, w0, w1, w2, w3);
      __syncwarp();
      if (lane == 0 && pc >= 0) mbar_arrive(BAR(B_U + pc));
    }
    __syncwarp();
    if (lane == 0) mbar_arrive(BAR(B_PREPD));
    if (bid < NCS) {
      mbar_wait(BAR(B_CW), 0);
      mbar_wait(BAR(B_SIGE + 1), 0);
      if (bid < 86) {
        const uint32_t wa = sb + OFF_CW + h * 8192 + ((lane >> 4) * 8 + (lane & 7)) * 64 + ((((lane >> 3) & 1) ^ ((lane & 7) >> 1)) * 16);
        float d0[4] = {0.f, 0.f, 0.f, 0.f}, d1[4] = {0.f, 0.f, 0.f, 0.f};
#pragma unroll 2
        for (int j = 0; j < 8; j++) {
          uint32_t a0, a1, a2, a3;
          ldsm4t(wa + j * 1024, a0, a1, a2, a3); mma_ones(d0, a0, a1, a2, a3);
          ldsm4t((wa ^ 32) + j * 1024, a0, a1, a2, a3); mma_ones(d1, a0, a1, a2, a3);
        }
        sts32(sb + OFF_CS + h * 128 + (q * 8 + g) * 4, __float_as_uint(q & 2 ? (q & 1 ? d1[2] : d1[0]) : (q & 1 ? d0[2] : d0[0])));
      } else {
        const int t = bid - 86, which = t >= 12, uu = (t - which * 12) >> 2, k0 = (t & 3) * 128 + h * 32 + g;
        uint16_t* d = p.scr->wX + (size_t)(uu * 2 + (q >> 1)) * (D_ * 32) + k0 * 32 + ((which * 2 + (q & 1)) ^ (g >> 1)) * 8;
#pragma unroll
        for (int i = 0; i < 4; i++) *(uint4*)(d + i * 256) = lds128(sb + OFF_CW + h * 2048 + g * 64 + ((q ^ (g >> 1)) * 16) + i * 512);
      }
    }
    __syncwarp();
    if (lane == 0) mbar_arrive(BAR(B_CSD));
    const int ck = rank * 4 + h;
    const uint32_t sdst = mapa(sb + OFF_STX + (ck * 8 + g) * 8, q & 1), sbar = mapa(BAR(B_STX), q & 1);
#pragma unroll 1
    for (int w = 0; w < 2; w++) {
      uint32_t la = sb + OFF_A + w * 65536 + lane * 128 + ((ck ^ (lane & 7)) * 16);
      float s0 = 0.f, s1 = 0.f, q0 = 0.f, q1 = 0.f;
#pragma unroll 1
      for (int s = 0; s < 8; s++) {
        uint32_t m[8];
        mbar_wait(BAR(B_FULLA + w * 8 + s), 0);
        ldsm4t(la, m[0], m[1], m[2], m[3]); ldsm4t(la + 4096, m[4], m[5], m[6], m[7]);
        la += 8192;
#pragma unroll
        for (int i = 0; i < 8; i++) {
          const float d0 = blo(m[i]), d1 = bhi(m[i]);
          s0 += d0; s1 += d1; q0 = fmaf(d0, d0, q0); q1 = fmaf(d1, d1, q1);
        }
      }
      s0 += s1; q0 += q1;
#pragma unroll
      for (int o = 1; o < 4; o <<= 1) { s0 += __shfl_xor_sync(0xffffffffu, s0, o); q0 += __shfl_xor_sync(0xffffffffu, q0, o); }
      const float md = s0 * (1.f / D_), var = fmaxf(fmaf(-md, md, q0 * (1.f / D_)), 0.f);
      if (q < 2) asm volatile("st.async.weak.shared::cluster.mbarrier::complete_tx::bytes.v2.f32 [%0], {%1,%2}, [%3];"
                              :: "r"(sdst + w * 512), "f"(-md), "f"(rsqrtf(var + 1e-5f)), "r"(sbar + w * 8) : "memory");
    }
  } else {
    asm volatile("setmaxnreg.dec.sync.aligned.u32 %0;" :: "n"(REG_M));
    const int h = warp - 12;
    asm volatile("barrier.cluster.wait.aligned;" ::: "memory");
    if (h == 0) {
      if (elect()) {
        mbar_wait(BAR(B_XR), 0);
        kv_load(1, pair);
        mbar_wait(BAR(B_TAP), 0);
        kv_load(2, pair); kv_load(3, pair);
        const int cw = js * 64, c3 = 1024 + js * 32, co = cw ^ 64, b3 = js < 6 ? 12288 : 8192;
        const uint16_t* wx = p.scr->wX + (size_t)js * (D_ * 32);
        mbar_wait(BAR(B_GO), 0);
        mbar_wait(BAR(B_KV + 3), 0);
        const int jp = js >> 1, xa = jp == 2 ? 0 : jp == 1 ? 2 : 1, xc = jp == 1 ? 0 : jp == 2 ? 1 : 2;
        const uint16_t* hs0 = p.scr->H + (size_t)tile * (86 * 1024);
        static_for<0, SCHED_N>([&](auto ic) {
          constexpr int it = decltype(ic)::v, r = SCHED[it];
          if constexpr (r == 3) {
            if (bid < NCS) {
              mbar_wait(BAR(B_PREPD), 0);
              fence_async_s();
              const bool up = bid < 86 ? bid >= 43 : bid >= 98;
              const int nb = bid < 86 ? 8 : 2, t = bid - (up ? 98 : 86);
              const int col = (bid < 86 ? bid - (up ? 43 : 0) : 40 + (t >> 2)) * 32, k0 = bid < 86 ? 0 : (t & 3) * 128;
              mbar_expect(BAR(B_CW), nb * 4096);
#pragma unroll 1
              for (int i = 0; i < nb; i++) tma2d(sb + OFF_CW + i * 4096, up ? &tmU32 : &tmG32, col, k0 + i * 64, BAR(B_CW));
            }
            mbar_wait(BAR(B_GO + 1), 0);
            fence_async_s();
            mbar_wait(BAR(B_FULLA + 3), 0);
          }
          if constexpr (r == 10) asm volatile("cp.async.bulk.prefetch.L2.global [%0], %1;" :: "l"((const char*)p.wd + (size_t)bid * 11008), "r"(11008) : "memory");
          if constexpr (r == 16) { mbar_wait(BAR(B_CS), 0); fence_async_g(); }
          if constexpr (r == 31) mbar_wait(BAR(B_GOH), 0);
          constexpr int w = r & 1, hs = (r - 64) >> 1;
          if constexpr (r >= 64) {
            if constexpr (hs != 9) mbar_wait(BAR(B_EMPTYA + w * 6 + h_slot(hs)), hs >= 6);
          } else if constexpr (r >= 6) mbar_wait(BAR(B_EMPTYR + r % 6), (r / 6 - 1) & 1);
          static_for<SchedDep<it - 1>::v + 1, SchedDep<it>::v + 1>([&](auto jc) {
            constexpr int j = decltype(jc)::v, o = SCHED[j], os = (o - 64) >> 1;
            if constexpr (!SchedReused<j, it>::v && o < 64 + 20) {
              if constexpr (o < 64) mbar_wait(BAR(B_FULLR + o % 6), (o / 6) & 1);
              else mbar_wait(BAR(B_FULLA + (o & 1) * 8 + h_slot(os)), h_par(os));
            }
          });
          const uint32_t b = BAR(B_FULLR + r % 6), d = sb + OFF_RING + (r % 6) * 16384;
          if constexpr (r >= 64) {
            const uint32_t fb = BAR(B_FULLA + w * 8 + h_slot(hs));
            const uint32_t hd = sb + OFF_A + w * 65536 + h_slot(hs) * 8192;
            const uint16_t* hw_ = hs0 + (size_t)w * (16 * 86 * 1024);
            if constexpr (hs < 9) {
              mbar_expect(fb, 8192);
              if constexpr (w == 0 && (hs == 0 || (hs >= 3 && hs < 6))) { mbar_wait(hs == 0 ? BAR(B_SEEN) : BAR(B_SEENP + hs - 3), 0); fence_async_g(); }
              bulk_ld(hd, hw_ + (hs < 6 ? hs / 3 * 8 + ((js + 2 * (hs % 3) + 2) & 7) : 16 + ((jp + hs - 5) & 3)) * 4096, 8192, fb);
            } else if constexpr (hs == 9) {
              mbar_expect(fb, 8192);
              bulk_ld(hd, hw_ + (40 + xa) * 2048, 4096, fb); bulk_ld(hd + 4096, hw_ + (40 + xc) * 2048, 4096, fb);
            } else if (jp == 3) {
              mbar_expect(fb, 4096);
              bulk_ld(hd, hw_ + 40 * 2048, 4096, fb);
            }
          } else if constexpr (r < 16) {
            mbar_expect(b, 16384);
            tma2d(d, &tmG, cw + (r >> 3) * 512, (r & 7) * 64, b); tma2d(d + 8192, &tmU, cw + (r >> 3) * 512, (r & 7) * 64, b);
          } else if constexpr (r < 24) {
            mbar_expect(b, b3);
            tma2d(d, &tmG32, c3, (r & 7) * 64, b); tma2d(d + 4096, &tmU32, c3, (r & 7) * 64, b);
            if (js < 6) bulk_ld(d + 8192, wx + (r & 7) * 2048, 4096, b);
          } else if constexpr (r < 33 && r != 29) {
            constexpr int rr = r - (r > 29);
            const int k = ((rr & 4) * 2 + ((js + 2 * (rr & 3)) & 7)) * 64;
            mbar_expect(b, 16384);
            tma2d(d, &tmD, cw, k, b); tma2d(d + 8192, &tmD, co, k, b);
          } else if constexpr (r == 29) {
            mbar_expect(b, 12288);
            tma2d(d, &tmD16, cw, c3, b); tma2d(d + 2048, &tmD16, cw, c3 + 16, b);
            tma2d(d + 8192, &tmD16, co, c3, b); tma2d(d + 10240, &tmD16, co, c3 + 16, b);
            tma2d(d + 4096, &tmD16, cw, jp < 3 ? 1280 + js * 16 : 1280, b);
            tma2d(d + (jp < 3 ? 12288 : 6144), &tmD16, jp < 3 ? co : cw, jp < 3 ? 1280 + js * 16 : 1296, b);
          } else if constexpr (r == 33) {
            mbar_expect(b, 16384);
            tma2d(d, &tmD, cw, 1024 + ((jp + 1) & 3) * 64, b); tma2d(d + 8192, &tmD, cw, 1024 + ((jp + 2) & 3) * 64, b);
          } else {
            mbar_expect(b, 16384);
            tma2d(d, &tmD, cw, 1024 + ((jp + 3) & 3) * 64, b);
            tma2d(d + 8192, &tmD16, cw, 1280 + xa * 32, b); tma2d(d + 10240, &tmD16, cw, 1296 + xa * 32, b);
            tma2d(d + 12288, &tmD16, cw, 1280 + xc * 32, b); tma2d(d + 14336, &tmD16, cw, 1296 + xc * 32, b);
          }
        });
      }
    } else if (h == 3) {
      unsigned* cnt = p.scr->cnt;
      unsigned* ch = cnt + (CNT_H + tile * 2) * 32;
      if (elect()) {
        mbar_wait_bounded(BAR(B_SIGX), 0);
        fence_async_s();
        asm volatile("cp.async.bulk.tensor.2d.global.shared::cta.bulk_group [%0, {%2, %3}], [%1];" :: "l"(&tmX), "r"(sb + OFF_XST), "r"(xb * 64), "r"(0) : "memory");
        asm volatile("cp.async.bulk.global.shared::cta.bulk_group [%0], [%1], 64;" :: "l"(p.scr->st1 + xb * 16), "r"(sb + OFF_CS) : "memory");
        asm volatile("cp.async.bulk.commit_group;" ::: "memory");
        asm volatile("cp.async.bulk.wait_group 0;" ::: "memory");
        fence_async_g();
        signal_gpu(cnt + CNT_X * 32);
        mbar_arrive(BAR(B_GO));
        mbar_wait_bounded(BAR(B_SIGE + 1), 0);
        signal_gpu(cnt + (CNT_E + 1) * 32);
        mbar_arrive(BAR(B_GO + 1));
      }
      __syncwarp();
      if (bid < NCS) pub_cs();
      if (elect()) {
        mbar_wait_bounded(BAR(B_SIGH), 0);
        signal_gpu(ch);
        mbar_wait_bounded(BAR(B_SIGH + 1), 0);
        signal_gpu(ch + 32 + (js >> 1));
        mbar_arrive(BAR(B_GOH));
        mbar_wait_bounded(BAR(B_SIG + 5), 0);
      }
    } else {
      const unsigned ep = p.scr->epoch[blockIdx.x] + 1;
      const int w = h - 1, blk = tile + 16 * w;
      const uint32_t aw = sb + OFF_A + w * 65536;
      const uint32_t fullA = BAR(B_FULLA + w * 8);
      if (elect()) {
#pragma unroll
        for (int s = 0; s < 8; s++) mbar_expect(fullA + s * 8, 8192);
        if (w == 0) {
          uint32_t b = BAR(B_XT);
          mbar_expect(b, 12288); mbar_expect(b + 8, 12288);
          mbar_wait(BAR(B_GO), 0);
          fence_async_s();
          poll1(&p.scr->cnt[CNT_X * 32], ep * NCTA);
          fence_async_g();
          bulk_ld(sb + OFF_XTE, p.scr->xT + (size_t)bid * 8192, 8192, b);
          bulk_ld(sb + OFF_STE, p.scr->st1, 4096, b);
          bulk_ld(sb + OFF_XTL, p.scr->xT + (size_t)bid * 8192 + 4096, 8192, b + 8);
          bulk_ld(sb + OFF_STL, p.scr->st1 + 1024, 4096, b + 8);
        }
        const uint16_t* asrc = p.scr->hT + (size_t)blk * (D_ * 64);
        const unsigned* hc = &p.scr->cnt[(CNT_H + tile * 2) * 32];
        mbar_wait(BAR(B_SIGE), 0);
        if (w == 1) { signal_gpu(&p.scr->cnt[CNT_E * 32]); mbar_wait(BAR(B_GO + 1), 0); }
        fence_async_s();
        poll1(&p.scr->cnt[(CNT_E + w) * 32], ep * NCTA);
        fence_async_g();
#pragma unroll
        for (int s = 0; s < 8; s++) {
          if (s == 3 && w == 0) { mbar_wait(BAR(B_CSD), 0); fence_async_s(); }
          if (s >= 4 && w == 0) mbar_wait(fullA + (s - 4) * 8, 0);
          if (s >= 2 && w == 1) mbar_wait(fullA + (s - 2) * 8, 0);
          bulk_ld(aw + s * 8192, asrc + s * 4096, 8192, fullA + s * 8);
        }
        if (w == 0) {
          poll1(&p.scr->cnt[CNT_C * 32], ep * NCS);
          fence_async_g(); fence_async_s();
          uint32_t b = BAR(B_CS), d = sb + OFF_CS;
          mbar_expect(b, (js < 6 ? 704 : 640));
          bulk_ld(d, p.scr->cs + js * 64, 256, b);
          bulk_ld(d + 256, p.scr->cs + (512 + js * 64), 256, b);
          bulk_ld(d + 512, p.scr->cs + (1024 + js * 32), 128, b);
          if (js < 6) bulk_ld(d + 640, p.scr->cs + (1280 + js * 16), 64, b);
        }
        if (w == 1) {
          mbar_wait(BAR(B_SIGH), 0);
          poll1(hc, ep * 8);
          mbar_arrive(BAR(B_SEEN));
          mbar_wait(BAR(B_SIGH + 1), 0);
          for (int m = 0; m < 3;) {
            uint4 v;
            asm volatile("ld.relaxed.gpu.global.v4.u32 {%0,%1,%2,%3}, [%4];" : "=r"(v.x), "=r"(v.y), "=r"(v.z), "=r"(v.w) : "l"(hc + 32) : "memory");
            const unsigned t2 = ep * 2;
            unsigned ok = ((int)(v.x - t2) >= 0) | (((int)(v.y - t2) >= 0) << 1) | (((int)(v.z - t2) >= 0) << 2) | (((int)(v.w - t2) >= 0) << 3);
            ok = (ok * 17) >> ((js >> 1) + 1);
            asm volatile("fence.acquire.gpu;" ::: "memory");
            while (m < 3 && ((ok >> m) & 1)) { mbar_arrive(BAR(B_SEENP + m)); m++; }
          }
          p.scr->epoch[blockIdx.x] = ep;
        }
      }
    }
  }
}

typedef CUresult (*EncFn)(CUtensorMap*, CUtensorMapDataType, cuuint32_t, void*, const cuuint64_t*, const cuuint64_t*,
                          const cuuint32_t*, const cuuint32_t*, CUtensorMapInterleave, CUtensorMapSwizzle,
                          CUtensorMapL2promotion, CUtensorMapFloatOOBfill);

void make_map(EncFn fn, CUtensorMap* tm, const void* ptr, int w, int hgt, int bw, int bh, CUtensorMapSwizzle sw, CUtensorMapL2promotion pr) {
  cuuint64_t dims[2] = {(cuuint64_t)w, (cuuint64_t)hgt};
  cuuint64_t str[1] = {(cuuint64_t)w * 2};
  cuuint32_t box[2] = {(cuuint32_t)bw, (cuuint32_t)bh}, es[2] = {1, 1};
  fn(tm, CU_TENSOR_MAP_DATA_TYPE_BFLOAT16, 2, (void*)ptr, dims, str, box, es, CU_TENSOR_MAP_INTERLEAVE_NONE, sw, pr,
     CU_TENSOR_MAP_FLOAT_OOB_FILL_NONE);
}

void make_map_runs(EncFn fn, CUtensorMap* tm, const void* ptr) {
  cuuint64_t dims[3] = {(cuuint64_t)D_, (cuuint64_t)(S_ / 8), 8};
  cuuint64_t str[2] = {(cuuint64_t)D_ * 16, (cuuint64_t)D_ * 2};
  cuuint32_t box[3] = {8, 33, 8}, es[3] = {1, 1, 1};
  fn(tm, CU_TENSOR_MAP_DATA_TYPE_BFLOAT16, 3, (void*)ptr, dims, str, box, es, CU_TENSOR_MAP_INTERLEAVE_NONE,
     CU_TENSOR_MAP_SWIZZLE_NONE, CU_TENSOR_MAP_L2_PROMOTION_L2_128B, CU_TENSOR_MAP_FLOAT_OOB_FILL_NONE);
}

}

extern "C" void kernel_launch(void* const* d_in, const int* in_sizes, int n_in, void* d_out, int out_size) {
  (void)in_sizes; (void)n_in; (void)out_size;
  static EncFn fn = nullptr;
  if (!fn) {
    void* f = nullptr; cudaDriverEntryPointQueryResult qr;
    cudaGetDriverEntryPoint("cuTensorMapEncodeTiled", &f, cudaEnableDefault, &qr);
    fn = (EncFn)f;
    cudaFuncSetAttribute(fused_kernel, cudaFuncAttributeMaxDynamicSharedMemorySize, SMEM_BYTES);
  }
  CUtensorMap tmK, tmV, tmG, tmU, tmG32, tmU32, tmD, tmX, tmXR, tmT, tmD16;
  void* xT = nullptr;
  cudaGetSymbolAddress(&xT, g_scr);
  make_map(fn, &tmX, xT, 8192, 128, 64, 128, CU_TENSOR_MAP_SWIZZLE_NONE, CU_TENSOR_MAP_L2_PROMOTION_NONE);
  {
    cuuint64_t dims[3] = {128, 16, (cuuint64_t)D_}, str[2] = {256, (cuuint64_t)S_ * 2};
    cuuint32_t box[3] = {128, 17, 2}, es[4] = {1, 1, 1, 1};
    fn(&tmT, CU_TENSOR_MAP_DATA_TYPE_BFLOAT16, 3, d_in[4], dims, str, box, es, CU_TENSOR_MAP_INTERLEAVE_NONE,
       CU_TENSOR_MAP_SWIZZLE_NONE, CU_TENSOR_MAP_L2_PROMOTION_NONE, CU_TENSOR_MAP_FLOAT_OOB_FILL_NONE);
    cuuint64_t dims4[4] = {64, 16, 128, 8}, str4[3] = {1024, 16384, 128};
    cuuint32_t box4[4] = {64, 2, 8, 8};
    fn(&tmXR, CU_TENSOR_MAP_DATA_TYPE_BFLOAT16, 4, d_in[0], dims4, str4, box4, es, CU_TENSOR_MAP_INTERLEAVE_NONE,
       CU_TENSOR_MAP_SWIZZLE_128B, CU_TENSOR_MAP_L2_PROMOTION_L2_256B, CU_TENSOR_MAP_FLOAT_OOB_FILL_NONE);
  }
  make_map_runs(fn, &tmK, d_in[1]);
  make_map_runs(fn, &tmV, d_in[2]);
  make_map(fn, &tmG, d_in[7], F_, D_, 64, 64, CU_TENSOR_MAP_SWIZZLE_128B, CU_TENSOR_MAP_L2_PROMOTION_NONE);
  make_map(fn, &tmU, d_in[8], F_, D_, 64, 64, CU_TENSOR_MAP_SWIZZLE_128B, CU_TENSOR_MAP_L2_PROMOTION_NONE);
  make_map(fn, &tmG32, d_in[7], F_, D_, 32, 64, CU_TENSOR_MAP_SWIZZLE_64B, CU_TENSOR_MAP_L2_PROMOTION_L2_256B);
  make_map(fn, &tmU32, d_in[8], F_, D_, 32, 64, CU_TENSOR_MAP_SWIZZLE_64B, CU_TENSOR_MAP_L2_PROMOTION_L2_256B);
  make_map(fn, &tmD, d_in[9], D_, F_, 64, 64, CU_TENSOR_MAP_SWIZZLE_128B, CU_TENSOR_MAP_L2_PROMOTION_NONE);
  make_map(fn, &tmD16, d_in[9], D_, F_, 64, 16, CU_TENSOR_MAP_SWIZZLE_128B, CU_TENSOR_MAP_L2_PROMOTION_NONE);
  Params p;
  p.shift_k = (const uint16_t*)d_in[3]; p.ssm_D = (const uint16_t*)d_in[5];
  p.wd = (const uint16_t*)d_in[9]; p.out = (uint16_t*)d_out; p.scr = (Scratch*)xT; p.z64 = 0;
  for (int cl = 0; cl < NCTA / 2; cl++) {
    const int pr = cl < 4 ? cl : cl < 36 ? 4 + ((cl - 4) & 7) * 4 + ((cl - 4) >> 3) : 36 + ((cl - 36) % 7) * 4 + (cl - 36) / 7;
    p.map[2 * cl] = (uint8_t)(2 * pr); p.map[2 * cl + 1] = (uint8_t)(2 * pr + 1);
  }
  cudaLaunchConfig_t cfg = {};
  cfg.gridDim = dim3(NCTA); cfg.blockDim = dim3(NTHR); cfg.dynamicSmemBytes = SMEM_BYTES; cfg.stream = cudaStreamPerThread;
  cudaLaunchAttribute at[1];
  at[0].id = cudaLaunchAttributeClusterDimension; at[0].val.clusterDim.x = 2; at[0].val.clusterDim.y = 1; at[0].val.clusterDim.z = 1;
  cfg.attrs = at; cfg.numAttrs = 1;
  cudaLaunchKernelEx(&cfg, fused_kernel, p, tmXR, tmT, tmK, tmV, tmG, tmU, tmG32, tmU32, tmD, tmX, tmD16);
}
```
